```python
import torch

def _softmax(x, axis=-1):
    return torch.softmax(x, dim=axis)
def _gelu(x):
    return torch.nn.functional.gelu(x, approximate="tanh")
def _silu(x):
    return torch.nn.functional.silu(x)
def _sigmoid(x):
    return torch.sigmoid(x)
def _layernorm(x, axis=-1, eps=1e-5):
    m = x.mean(dim=axis, keepdim=True)
    v = x.var(dim=axis, keepdim=True, unbiased=False)
    return (x - m) / torch.sqrt(v + eps)
def _scatter_add(tgt, idx, src, axis=0):
    return tgt.clone().index_add_(axis, idx, src)
def _segment_sum(src, seg, n):
    out = torch.zeros((n,) + src.shape[1:], dtype=src.dtype)
    return out.index_add_(0, seg, src)
def _pad(x, pw):
    flat = tuple(v for pair in reversed(pw) for v in pair)
    return torch.nn.functional.pad(x, flat)

kernel_name = 'concat_heads__mha_block_cached__mha_block_cached__near_ridge'

def setup_inputs():

    _w = (lambda a: (lambda t: t.to(torch.bfloat16) if t.is_floating_point() else t)(torch.as_tensor(a)))
    def _A_setup():
        B, Sq, D = 16, 160, 1024
        H, Sk, Dh = 32, 512, 128
        return {
            "x": _w((lambda *s: torch.randn(*s, dtype=torch.bfloat16) * 0.8)(B, Sq, D)),
            "k_cache": _w((lambda *s: torch.randn(*s, dtype=torch.bfloat16) * 0.8)(B, H, Sk, Dh)),
            "v_cache": _w((lambda *s: torch.randn(*s, dtype=torch.bfloat16) * 0.05)(B, H, Sk, Dh)),
            "wq": _w((lambda *s: torch.randn(*s, dtype=torch.bfloat16) * 0.8)(D, H * Dh) * (D ** -0.5)),
            "wo": _w((lambda *s: torch.randn(*s, dtype=torch.bfloat16) * 0.05)(H * Dh, D) * ((H * Dh) ** -0.5)),
        }
    _A_in = _A_setup()

    def _B_setup():
        B, Sq, D = 16, 160, 1024
        H, Sk, Dh = 32, 512, 128
        return {
            "x": _w((lambda *s: torch.randn(*s, dtype=torch.bfloat16) * 0.8)(B, Sq, D)),
            "k_cache": _w((lambda *s: torch.randn(*s, dtype=torch.bfloat16) * 0.8)(B, H, Sk, Dh)),
            "v_cache": _w((lambda *s: torch.randn(*s, dtype=torch.bfloat16) * 0.05)(B, H, Sk, Dh)),
            "wq": _w((lambda *s: torch.randn(*s, dtype=torch.bfloat16) * 0.8)(D, H * Dh) * (D ** -0.5)),
            "wo": _w((lambda *s: torch.randn(*s, dtype=torch.bfloat16) * 0.05)(H * Dh, D) * ((H * Dh) ** -0.5)),
        }
    _B_in = _B_setup()

    return {
        "A_x": _A_in["x"],
        "A_k_cache": _A_in["k_cache"],
        "A_v_cache": _A_in["v_cache"],
        "A_wq": _A_in["wq"],
        "A_wo": _A_in["wo"],
        "B_x": _B_in["x"],
        "B_k_cache": _B_in["k_cache"],
        "B_v_cache": _B_in["v_cache"],
        "B_wq": _B_in["wq"],
        "B_wo": _B_in["wo"],
    }

def reference(A_x, A_k_cache, A_v_cache, A_wq, A_wo, B_x, B_k_cache, B_v_cache, B_wq, B_wo):
    def _A_ref(x, k_cache, v_cache, wq, wo):
        B, Sq, D = x.shape
        H, Dh = 32, 128
        q = (lambda x, *d: x.permute(*d))((x @ wq).reshape(B, Sq, H, Dh), 0, 2, 1, 3)
        scores = torch.einsum("bhqd,bhkd->bhqk", q, k_cache) * (Dh ** -0.5)
        p = _softmax(scores, axis=-1)
        o = torch.einsum("bhqk,bhkd->bhqd", p, v_cache)
        return (lambda x, *d: x.permute(*d))(o, 0, 2, 1, 3).reshape(B, Sq, H * Dh) @ wo

    def _B_ref(x, k_cache, v_cache, wq, wo):
        B, Sq, D = x.shape
        H, Dh = 32, 128
        q = (lambda x, *d: x.permute(*d))((x @ wq).reshape(B, Sq, H, Dh), 0, 2, 1, 3)
        scores = torch.einsum("bhqd,bhkd->bhqk", q, k_cache) * (Dh ** -0.5)
        p = _softmax(scores, axis=-1)
        o = torch.einsum("bhqk,bhkd->bhqd", p, v_cache)
        return (lambda x, *d: x.permute(*d))(o, 0, 2, 1, 3).reshape(B, Sq, H * Dh) @ wo

    a = _A_ref(A_x, A_k_cache, A_v_cache, A_wq, A_wo)
    b = _B_ref(B_x, B_k_cache, B_v_cache, B_wq, B_wo)
    return torch.concatenate([a, b], axis=-1)
```

```cpp
#include <cuda_runtime.h>
#include <cuda_bf16.h>
#include <cuda.h>
#include <stdint.h>

namespace {

constexpr int SQ = 160, NH = 32, SK = 512, DH = 128, NBATCH = 16;
constexpr int XSLOT = 20480;
constexpr int RSLOT = 16384;
constexpr int NRING = 9;
constexpr int SM_XQ = 0;
constexpr int SM_RING = 4 * XSLOT;
constexpr int SM_BAR = SM_RING + NRING * RSLOT;
constexpr int BAR_FULL = SM_BAR;
constexpr int BAR_EMPTY = SM_BAR + 72;
constexpr int BAR_PEMPTY = SM_BAR + 144;
constexpr int BAR_XFULL = SM_BAR + 216;
constexpr int BAR_XEMPTY = SM_BAR + 248;
constexpr int SM_ABORT = SM_BAR + 1016;
constexpr int SMEM_BYTES = SM_BAR + 1024 + 1024;
constexpr int NTHREADS = 512;
constexpr int NCTA = 128;
#define STAGGER 1
constexpr uint32_t SPIN_LIMIT = 1u << 22;

struct __align__(64) KParams {
  CUtensorMap x[2], wq[2], k[2], v[2], wo[2], o, out;
};

__device__ __nv_bfloat16 g_o[2 * NBATCH * SQ * NH * DH];
__device__ unsigned int g_flags[256];

#define PROF(idx)
#define PROF2(n, idx)
#define PROF3(g, idx)
__device__ __forceinline__ uint32_t smem_u32(const void* p) { return (uint32_t)__cvta_generic_to_shared(p); }
__device__ __forceinline__ void mbar_init(uint32_t bar, uint32_t cnt) {
  asm volatile("mbarrier.init.shared::cta.b64 [%0], %1;" ::"r"(bar), "r"(cnt));
}
__device__ __forceinline__ void mbar_expect_tx(uint32_t bar, uint32_t bytes) {
  asm volatile("mbarrier.arrive.expect_tx.shared::cta.b64 _, [%0], %1;" ::"r"(bar), "r"(bytes) : "memory");
}
__device__ __forceinline__ void mbar_arrive_if(uint32_t bar, bool pred) {
  asm volatile("{\n.reg .pred p;\nsetp.ne.b32 p, %1, 0;\n@p mbarrier.arrive.shared::cta.b64 _, [%0];\n}" ::"r"(bar), "r"((int)pred) : "memory");
}
__device__ __forceinline__ void mbar_arrive_remote_if(uint32_t remote_bar, bool pred) {
  asm volatile("{\n.reg .pred p;\nsetp.ne.b32 p, %1, 0;\n@p mbarrier.arrive.shared::cluster.b64 _, [%0];\n}" ::"r"(remote_bar), "r"((int)pred) : "memory");
}
__device__ __forceinline__ uint32_t mapa(uint32_t addr, uint32_t cta) {
  uint32_t r;
  asm("mapa.shared::cluster.u32 %0, %1, %2;" : "=r"(r) : "r"(addr), "r"(cta));
  return r;
}
__device__ __forceinline__ bool spin_giveup(uint32_t abort_addr, uint32_t& spins) {
  uint32_t ab;
  asm volatile("ld.volatile.shared.u32 %0, [%1];" : "=r"(ab) : "r"(abort_addr) : "memory");
  if (++spins > SPIN_LIMIT) {
    asm volatile("st.volatile.shared.u32 [%0], %1;" ::"r"(abort_addr), "r"(1u) : "memory");
    ab = 1;
  }
  return ab != 0;
}
__device__ __forceinline__ void mbar_wait(uint32_t bar, uint32_t parity) {
  uint32_t ok, spins = 0;
  while (true) {
    asm volatile("{\n.reg .pred p;\nmbarrier.try_wait.parity.shared::cta.b64 p, [%1], %2;\nselp.u32 %0, 1, 0, p;\n}"
                 : "=r"(ok) : "r"(bar), "r"(parity) : "memory");
    if (ok) break;
    if (spin_giveup((bar & ~1023u) + 1016u, spins)) break;
  }
}
__device__ __forceinline__ void tma_2d(uint32_t dst, const CUtensorMap* tm, uint32_t bar, int c0, int c1) {
  asm volatile("cp.async.bulk.tensor.2d.shared::cluster.global.mbarrier::complete_tx::bytes [%0], [%1, {%3, %4}], [%2];"
               ::"r"(dst), "l"(tm), "r"(bar), "r"(c0), "r"(c1) : "memory");
}
__device__ __forceinline__ void tma_2d_hint(uint32_t dst, const CUtensorMap* tm, uint32_t bar, int c0, int c1, uint64_t pol) {
  asm volatile("cp.async.bulk.tensor.2d.shared::cluster.global.mbarrier::complete_tx::bytes.L2::cache_hint [%0], [%1, {%3, %4}], [%2], %5;"
               ::"r"(dst), "l"(tm), "r"(bar), "r"(c0), "r"(c1), "l"(pol) : "memory");
}
__device__ __forceinline__ void tma_2d_mc(uint32_t dst, const CUtensorMap* tm, uint32_t bar, int c0, int c1, uint16_t mask) {
  asm volatile("cp.async.bulk.tensor.2d.shared::cluster.global.mbarrier::complete_tx::bytes.multicast::cluster [%0], [%1, {%3, %4}], [%2], %5;"
               ::"r"(dst), "l"(tm), "r"(bar), "r"(c0), "r"(c1), "h"(mask) : "memory");
}
__device__ __forceinline__ void tma_5d_mc(uint32_t dst, const CUtensorMap* tm, uint32_t bar, int c0, int c4, uint16_t mask) {
  asm volatile("cp.async.bulk.tensor.5d.shared::cluster.global.mbarrier::complete_tx::bytes.multicast::cluster [%0], [%1, {%3, %4, %4, %4, %5}], [%2], %6;"
               ::"r"(dst), "l"(tm), "r"(bar), "r"(c0), "r"(0), "r"(c4), "h"(mask) : "memory");
}
__device__ __forceinline__ void tma_store_2d(const CUtensorMap* tm, uint32_t src, int c0, int c1) {
  asm volatile("cp.async.bulk.tensor.2d.global.shared::cta.bulk_group [%0, {%2, %3}], [%1];"
               ::"l"(tm), "r"(src), "r"(c0), "r"(c1) : "memory");
}
__device__ __forceinline__ void wg_fence() { asm volatile("wgmma.fence.sync.aligned;" ::: "memory"); }
__device__ __forceinline__ void wg_commit() { asm volatile("wgmma.commit_group.sync.aligned;" ::: "memory"); }
template <int N> __device__ __forceinline__ void wg_wait() { asm volatile("wgmma.wait_group.sync.aligned %0;" ::"n"(N) : "memory"); }
template <int N> __device__ __forceinline__ void fence_regs(float (&a)[N]) {
#pragma unroll
  for (int i = 0; i < N; i++) asm volatile("" : "+f"(a[i])::"memory");
}
template <int N> __device__ __forceinline__ void fence_regs(uint32_t (&a)[N]) {
#pragma unroll
  for (int i = 0; i < N; i++) asm volatile("" : "+r"(a[i])::"memory");
}
__device__ __forceinline__ uint64_t make_desc(uint32_t addr, uint32_t lbo, uint32_t sbo) {
  uint32_t lo = ((addr & 0x3FFFF) >> 4) | ((lbo >> 4) << 16);
  uint32_t hi = (sbo >> 4) | (1u << 30);
  return ((uint64_t)hi << 32) | lo;
}
__device__ __forceinline__ uint32_t pack_bf16(float lo, float hi) {
  uint32_t r;
  asm("cvt.rn.bf16x2.f32 %0, %1, %2;" : "=r"(r) : "f"(hi), "f"(lo));
  return r;
}
__device__ __forceinline__ float ex2(float x) {
  float y;
  asm("ex2.approx.ftz.f32 %0, %1;" : "=f"(y) : "f"(x));
  return y;
}
__device__ __forceinline__ void stsm_x4_t(uint32_t addr, uint32_t r0, uint32_t r1, uint32_t r2, uint32_t r3) {
  asm volatile("stmatrix.sync.aligned.m8n8.x4.trans.shared.b16 [%0], {%1, %2, %3, %4};" ::"r"(addr), "r"(r0), "r"(r1), "r"(r2), "r"(r3) : "memory");
}
__device__ __forceinline__ void stsm_x2_t(uint32_t addr, uint32_t r0, uint32_t r1) {
  asm volatile("stmatrix.sync.aligned.m8n8.x2.trans.shared.b16 [%0], {%1, %2};" ::"r"(addr), "r"(r0), "r"(r1) : "memory");
}
__device__ __forceinline__ void bar_sync(int id, int n) { asm volatile("bar.sync %0, %1;" ::"r"(id), "r"(n) : "memory"); }
__device__ __forceinline__ void cluster_sync_all() {
  asm volatile("barrier.cluster.arrive.release;\nbarrier.cluster.wait.acquire;" ::: "memory");
}

template <int TA, int TB>
__device__ __forceinline__ void wgmma_ss_n160(float (&d)[80], uint64_t da, uint64_t db, int sd) {
  asm volatile("{\n.reg .pred p;\nsetp.ne.b32 p, %82, 0;\n"
    "wgmma.mma_async.sync.aligned.m64n160k16.f32.bf16.bf16 {"
    "%0, %1, %2, %3, %4, %5, %6, %7, %8, %9, %10, %11, %12, %13, %14, %15, %16, %17, %18, %19, %20, %21, %22, %23, %24, %25, %26, %27, %28, %29, %30, %31, "
    "%32, %33, %34, %35, %36, %37, %38, %39, %40, %41, %42, %43, %44, %45, %46, %47, %48, %49, %50, %51, %52, %53, %54, %55, %56, %57, %58, %59, %60, %61, "
    "%62, %63, %64, %65, %66, %67, %68, %69, %70, %71, %72, %73, %74, %75, %76, %77, %78, %79"
    "}, %80, %81, p, 1, 1, %83, %84;\n}\n"
    : "+f"(d[0]), "+f"(d[1]), "+f"(d[2]), "+f"(d[3]), "+f"(d[4]), "+f"(d[5]), "+f"(d[6]), "+f"(d[7]), "+f"(d[8]), "+f"(d[9]), "+f"(d[10]), "+f"(d[11]),
      "+f"(d[12]), "+f"(d[13]), "+f"(d[14]), "+f"(d[15]), "+f"(d[16]), "+f"(d[17]), "+f"(d[18]), "+f"(d[19]), "+f"(d[20]), "+f"(d[21]), "+f"(d[22]),
      "+f"(d[23]), "+f"(d[24]), "+f"(d[25]), "+f"(d[26]), "+f"(d[27]), "+f"(d[28]), "+f"(d[29]), "+f"(d[30]), "+f"(d[31]), "+f"(d[32]), "+f"(d[33]),
      "+f"(d[34]), "+f"(d[35]), "+f"(d[36]), "+f"(d[37]), "+f"(d[38]), "+f"(d[39]), "+f"(d[40]), "+f"(d[41]), "+f"(d[42]), "+f"(d[43]), "+f"(d[44]),
      "+f"(d[45]), "+f"(d[46]), "+f"(d[47]), "+f"(d[48]), "+f"(d[49]), "+f"(d[50]), "+f"(d[51]), "+f"(d[52]), "+f"(d[53]), "+f"(d[54]), "+f"(d[55]),
      "+f"(d[56]), "+f"(d[57]), "+f"(d[58]), "+f"(d[59]), "+f"(d[60]), "+f"(d[61]), "+f"(d[62]), "+f"(d[63]), "+f"(d[64]), "+f"(d[65]), "+f"(d[66]),
      "+f"(d[67]), "+f"(d[68]), "+f"(d[69]), "+f"(d[70]), "+f"(d[71]), "+f"(d[72]), "+f"(d[73]), "+f"(d[74]), "+f"(d[75]), "+f"(d[76]), "+f"(d[77]),
      "+f"(d[78]), "+f"(d[79])
    : "l"(da), "l"(db), "r"(sd), "n"(TA), "n"(TB));
}
template <int TA, int TB>
__device__ __forceinline__ void wgmma_ss_n56(float (&d)[28], uint64_t da, uint64_t db, int sd) {
  asm volatile("{\n.reg .pred p;\nsetp.ne.b32 p, %30, 0;\n"
    "wgmma.mma_async.sync.aligned.m64n56k16.f32.bf16.bf16 {"
    "%0, %1, %2, %3, %4, %5, %6, %7, %8, %9, %10, %11, %12, %13, %14, %15, %16, %17, %18, %19, %20, %21, %22, %23, %24, %25, %26, %27"
    "}, %28, %29, p, 1, 1, %31, %32;\n}\n"
    : "+f"(d[0]), "+f"(d[1]), "+f"(d[2]), "+f"(d[3]), "+f"(d[4]), "+f"(d[5]), "+f"(d[6]), "+f"(d[7]), "+f"(d[8]), "+f"(d[9]), "+f"(d[10]), "+f"(d[11]),
      "+f"(d[12]), "+f"(d[13]), "+f"(d[14]), "+f"(d[15]), "+f"(d[16]), "+f"(d[17]), "+f"(d[18]), "+f"(d[19]), "+f"(d[20]), "+f"(d[21]), "+f"(d[22]),
      "+f"(d[23]), "+f"(d[24]), "+f"(d[25]), "+f"(d[26]), "+f"(d[27])
    : "l"(da), "l"(db), "r"(sd), "n"(TA), "n"(TB));
}
template <int TA, int TB>
__device__ __forceinline__ void wgmma_ss_n64(float (&d)[32], uint64_t da, uint64_t db, int sd) {
  asm volatile("{\n.reg .pred p;\nsetp.ne.b32 p, %34, 0;\n"
    "wgmma.mma_async.sync.aligned.m64n64k16.f32.bf16.bf16 {"
    "%0, %1, %2, %3, %4, %5, %6, %7, %8, %9, %10, %11, %12, %13, %14, %15, %16, %17, %18, %19, %20, %21, %22, %23, %24, %25, %26, %27, %28, %29, %30, %31"
    "}, %32, %33, p, 1, 1, %35, %36;\n}\n"
    : "+f"(d[0]), "+f"(d[1]), "+f"(d[2]), "+f"(d[3]), "+f"(d[4]), "+f"(d[5]), "+f"(d[6]), "+f"(d[7]), "+f"(d[8]), "+f"(d[9]), "+f"(d[10]), "+f"(d[11]),
      "+f"(d[12]), "+f"(d[13]), "+f"(d[14]), "+f"(d[15]), "+f"(d[16]), "+f"(d[17]), "+f"(d[18]), "+f"(d[19]), "+f"(d[20]), "+f"(d[21]), "+f"(d[22]),
      "+f"(d[23]), "+f"(d[24]), "+f"(d[25]), "+f"(d[26]), "+f"(d[27]), "+f"(d[28]), "+f"(d[29]), "+f"(d[30]), "+f"(d[31])
    : "l"(da), "l"(db), "r"(sd), "n"(TA), "n"(TB));
}
template <int TB>
__device__ __forceinline__ void wgmma_rs_n128(float (&d)[64], uint32_t a0, uint32_t a1, uint32_t a2, uint32_t a3, uint64_t db, int sd) {
  asm volatile("{\n.reg .pred p;\nsetp.ne.b32 p, %69, 0;\n"
    "wgmma.mma_async.sync.aligned.m64n128k16.f32.bf16.bf16 {"
    "%0, %1, %2, %3, %4, %5, %6, %7, %8, %9, %10, %11, %12, %13, %14, %15, %16, %17, %18, %19, %20, %21, %22, %23, %24, %25, %26, %27, %28, %29, %30, %31, "
    "%32, %33, %34, %35, %36, %37, %38, %39, %40, %41, %42, %43, %44, %45, %46, %47, %48, %49, %50, %51, %52, %53, %54, %55, %56, %57, %58, %59, %60, %61, "
    "%62, %63"
    "}, {%64, %65, %66, %67}, %68, p, 1, 1, %70;\n}\n"
    : "+f"(d[0]), "+f"(d[1]), "+f"(d[2]), "+f"(d[3]), "+f"(d[4]), "+f"(d[5]), "+f"(d[6]), "+f"(d[7]), "+f"(d[8]), "+f"(d[9]), "+f"(d[10]), "+f"(d[11]),
      "+f"(d[12]), "+f"(d[13]), "+f"(d[14]), "+f"(d[15]), "+f"(d[16]), "+f"(d[17]), "+f"(d[18]), "+f"(d[19]), "+f"(d[20]), "+f"(d[21]), "+f"(d[22]),
      "+f"(d[23]), "+f"(d[24]), "+f"(d[25]), "+f"(d[26]), "+f"(d[27]), "+f"(d[28]), "+f"(d[29]), "+f"(d[30]), "+f"(d[31]), "+f"(d[32]), "+f"(d[33]),
      "+f"(d[34]), "+f"(d[35]), "+f"(d[36]), "+f"(d[37]), "+f"(d[38]), "+f"(d[39]), "+f"(d[40]), "+f"(d[41]), "+f"(d[42]), "+f"(d[43]), "+f"(d[44]),
      "+f"(d[45]), "+f"(d[46]), "+f"(d[47]), "+f"(d[48]), "+f"(d[49]), "+f"(d[50]), "+f"(d[51]), "+f"(d[52]), "+f"(d[53]), "+f"(d[54]), "+f"(d[55]),
      "+f"(d[56]), "+f"(d[57]), "+f"(d[58]), "+f"(d[59]), "+f"(d[60]), "+f"(d[61]), "+f"(d[62]), "+f"(d[63])
    : "r"(a0), "r"(a1), "r"(a2), "r"(a3), "l"(db), "r"(sd), "n"(TB));
}

struct PCursor {
  uint32_t slot, eph, pbits;
  __device__ __forceinline__ void adv() { if (++slot == NRING) { slot = 0; eph ^= 1; pbits |= 0x80000000u; } }
};

__device__ __forceinline__ int item_heads(bool stag, int item) { return (stag && (item == 0 || item == 4)) ? 1 : 2; }
__device__ __forceinline__ int item_head0(bool stag, int item) { return stag ? (item == 0 ? 0 : 2 * item - 1) : 2 * item; }
__device__ __forceinline__ int ph2_chunk(int kk) { return 4 * (4 * ((kk >> 2) & 3) + (kk >> 4)) + (kk & 3); }

__device__ __forceinline__ bool elect_one() {
  uint32_t pred;
  asm volatile("{\n.reg .pred p;\nelect.sync _|p, 0xffffffff;\nselp.u32 %0, 1, 0, p;\n}" : "=r"(pred));
  return pred != 0;
}

template <int MODE>
__device__ __forceinline__ void produce_w(const KParams& P, uint32_t sb, PCursor& c, int blk, uint32_t rank, int col0, int ks) {
#pragma unroll
  for (int h = 0; h < 2; ++h) {
    mbar_wait(sb + BAR_EMPTY + c.slot * 8, c.eph);
    const uint32_t fb = sb + BAR_FULL + c.slot * 8;
    if (h == (int)rank) {
      if (c.pbits >> 31) {
        mbar_wait(sb + BAR_PEMPTY + c.slot * 8, (c.pbits >> c.slot) & 1);
        c.pbits ^= 1u << c.slot;
      }
      const uint32_t dst = sb + SM_RING + c.slot * RSLOT;
      if (elect_one()) {
        mbar_expect_tx(fb, MODE == 1 ? 8192 : RSLOT);
        if (MODE == 0) {
          tma_2d_mc(dst, &P.wq[blk], fb, col0 + 128 * h, 64 * ks, 3);
          tma_2d_mc(dst + 8192, &P.wq[blk], fb, col0 + 128 * h + 64, 64 * ks, 3);
        } else if (MODE == 1) {
          tma_2d_mc(dst, &P.wq[blk], fb, col0 + 64 * h, 64 * ks, 3);
        } else {
          tma_5d_mc(dst, &P.wo[blk], fb, col0 + 128 * h, 2 * ks, 3);
          tma_5d_mc(dst + 8192, &P.wo[blk], fb, col0 + 128 * h + 64, 2 * ks, 3);
        }
      }
    } else {
      if (elect_one()) mbar_expect_tx(fb, MODE == 1 ? 8192 : RSLOT);
    }
    __syncwarp();
    c.adv();
  }
}

__device__ __forceinline__ void producer_ring(const KParams& P, uint32_t sb, int blk, int b, int j, uint32_t rank) {
  uint64_t pol_first;
  asm volatile("createpolicy.fractional.L2::evict_first.b64 %0, 1.0;" : "=l"(pol_first));
  PCursor c{0, 1, 0};
  const bool stag = STAGGER && (j & 1);
  const int nitems = stag ? 5 : 4;
#pragma unroll 1
  for (int item = 0; item < nitems; ++item) {
    const int nh = item_heads(stag, item), h0 = 8 * j + item_head0(stag, item);
    if (nh == 2) {
#pragma unroll 1
      for (int ks = 0; ks < 16; ++ks) produce_w<0>(P, sb, c, blk, rank, 128 * h0, ks);
    } else {
#pragma unroll 1
      for (int ks = 0; ks < 16; ++ks) produce_w<1>(P, sb, c, blk, rank, 128 * h0, ks);
    }
    int row = (b * NH + h0) * SK;
#pragma unroll 1
    for (int n = 0; n < 8 * nh; ++n, row += 64) {
#pragma unroll
      for (int kv = 0; kv < 2; ++kv) {
        mbar_wait(sb + BAR_EMPTY + c.slot * 8, c.eph);
        const uint32_t fb = sb + BAR_FULL + c.slot * 8;
        const uint32_t dst = sb + SM_RING + c.slot * RSLOT;
        const CUtensorMap* tm = kv == 0 ? &P.k[blk] : &P.v[blk];
        if (elect_one()) {
          mbar_expect_tx(fb, RSLOT);
          tma_2d_hint(dst, tm, fb, 0, row, pol_first);
          tma_2d_hint(dst + 8192, tm, fb, 64, row, pol_first);
        }
        __syncwarp();
        c.adv();
      }
    }
  }
#pragma unroll 1
  for (int kk = 0; kk < 64; ++kk) produce_w<2>(P, sb, c, blk, rank, 256 * j, ph2_chunk(kk));
}

__device__ __forceinline__ void producer_x(const KParams& P, uint32_t sb, int blk, int b, int j, const unsigned int* flags) {
  const unsigned int* fl = flags + (blk * NBATCH + b) * 8;
  unsigned int fbase;
  asm volatile("ld.relaxed.gpu.global.u32 %0, [%1];" : "=r"(fbase) : "l"(fl + 2 * j) : "memory");
  const int n1 = ((STAGGER && (j & 1)) ? 5 : 4) * 16;
#pragma unroll 1
  for (int xg = 0; xg < n1 + 64; ++xg) {
    const uint32_t xs = xg & 3;
    const int kk = xg - n1;
    if (kk >= 0 && (kk & 3) == 0 && ((kk >> 4) == 0 || (kk >> 4) == 3)) {
      const unsigned int* fp = fl + 2 * ((kk >> 2) & 3) + ((kk >> 4) == 3);
      uint32_t spins = 0;
      while (true) {
        unsigned int v;
        asm volatile("ld.acquire.gpu.global.u32 %0, [%1];" : "=r"(v) : "l"(fp) : "memory");
        if (v - fbase >= 3u) break;
        if (spin_giveup(sb + SM_ABORT, spins)) break;
      }
      asm volatile("fence.proxy.async;" ::: "memory");
    }
    mbar_wait(sb + BAR_XEMPTY + xs * 8, ((xg >> 2) & 1) ^ 1);
    const uint32_t xb = sb + BAR_XFULL + xs * 8;
    if (elect_one()) {
      mbar_expect_tx(xb, XSLOT);
      if (kk >= 0) tma_2d(sb + SM_XQ + xs * XSLOT, &P.o, xb, 0, ((blk * NBATCH + b) * 64 + ph2_chunk(kk)) * SQ);
      else tma_2d(sb + SM_XQ + xs * XSLOT, &P.x[blk], xb, 64 * (xg & 15), SQ * b);
    }
    __syncwarp();
  }
}

struct Cursor {
  uint32_t slot, ph;
  __device__ __forceinline__ void adv() { if (++slot == NRING) { slot = 0; ph ^= 1; } }
  __device__ __forceinline__ void adv2() { slot += 2; if (slot >= NRING) { slot -= NRING; ph ^= 1; } }
};

__device__ __forceinline__ void release_ring(uint32_t sb, uint32_t slot, bool remote, uint32_t psb, bool elected) {
  mbar_arrive_remote_if(psb + BAR_PEMPTY + slot * 8, remote && elected);
  mbar_arrive_if(sb + BAR_EMPTY + slot * 8, elected);
}

template <int NG>
__device__ __forceinline__ void store_T(const float* a, uint32_t base_lane, int ngroups) {
#pragma unroll
  for (int g = 0; g + 1 < NG; g += 2) {
    stsm_x4_t(base_lane + g * 1024, pack_bf16(a[4 * g], a[4 * g + 1]), pack_bf16(a[4 * g + 2], a[4 * g + 3]),
              pack_bf16(a[4 * g + 4], a[4 * g + 5]), pack_bf16(a[4 * g + 6], a[4 * g + 7]));
  }
  if (NG & 1) {
    if (ngroups == NG) {
      constexpr int g = NG - 1;
      stsm_x2_t(base_lane + g * 1024, pack_bf16(a[4 * g], a[4 * g + 1]), pack_bf16(a[4 * g + 2], a[4 * g + 3]));
    }
  }
}

struct AttnCtx {
  uint32_t sb, peer, rank;
  int wg, warp, lane, bb;
  bool elected;
  __nv_bfloat16* oscr;
};

__device__ __forceinline__ bool mbar_try(uint32_t bar, uint32_t parity) {
  uint32_t ok;
  asm volatile("{\n.reg .pred p;\nmbarrier.try_wait.parity.shared::cta.b64 p, [%1], %2;\nselp.u32 %0, 1, 0, p;\n}"
               : "=r"(ok) : "r"(bar), "r"(parity) : "memory");
  return ok != 0;
}

template <bool HALF>
__device__ __forceinline__ void attention(const AttnCtx& A, Cursor& cur, int item, int h0, int nh) {
  const uint32_t sb = A.sb, peer = A.peer, rank = A.rank;
  const int wg = A.wg, lane = A.lane;
  const bool elected = A.elected;
  const int nblk = 8 * nh;
  const float CS = 0.08838834764831845f * 1.4426950408889634f;
  (void)item;
  float o[64], s[32];
  uint32_t p[16], p2[16];
#pragma unroll
  for (int i = 0; i < 64; ++i) o[i] = 0.f;
#pragma unroll
  for (int i = 0; i < 32; ++i) s[i] = 0.f;
#pragma unroll
  for (int i = 0; i < 16; ++i) { p[i] = 0u; p2[i] = 0u; }
  float mc0 = 0.f, mc1 = 0.f, l0 = 0.f, l1 = 0.f;
  Cursor kc = cur, vc = cur; vc.adv();
  const uint64_t dq0 = make_desc(sb + SM_XQ + wg * 8192, 0, HALF ? 512 : 1024);
  const uint64_t dk0 = make_desc(sb + SM_RING, 0, 1024);
  const uint64_t dv0 = make_desc(sb + SM_RING, 8192, 1024);
  auto issue_qk = [&](int n) {
    const uint64_t dq = dq0 + (uint32_t)((n >> 3) * 2 * (XSLOT >> 4));
    const uint64_t dk = dk0 + kc.slot * (RSLOT >> 4);
    wg_fence();
#pragma unroll
    for (int kk = 0; kk < 8; ++kk)
      wgmma_ss_n64<0, 0>(s, dq + (kk >> 2) * (XSLOT >> 4) + (kk & 3) * 2, dk + (kk >> 2) * 512 + (kk & 3) * 2, kk != 0);
    wg_commit();
  };
  auto issue_pv = [&](int n, uint32_t (&pc)[16]) {
    const uint64_t dv = dv0 + vc.slot * (RSLOT >> 4);
    wg_fence();
#pragma unroll
    for (int kk = 0; kk < 4; ++kk)
      wgmma_rs_n128<1>(o, pc[4 * kk], pc[4 * kk + 1], pc[4 * kk + 2], pc[4 * kk + 3], dv + kk * 128, ((n & 7) | kk) != 0);
    wg_commit();
  };
  auto done_qk = [&](int n) {
    release_ring(sb, kc.slot, 2 * n + 9 >= 2 * nblk && rank == 0, peer, elected);
    kc.adv2();
    mbar_arrive_if(sb + BAR_XEMPTY + ((n >> 3) * 2) * 8, (n & 7) == 7 && elected);
    mbar_arrive_if(sb + BAR_XEMPTY + ((n >> 3) * 2 + 1) * 8, (n & 7) == 7 && elected);
  };
  auto softmax = [&](bool first, uint32_t (&pn)[16], float& al0, float& al1) -> bool {
    bool upd = first;
    while (true) {
      if (upd) {
        float t0[8], t1[8];
#pragma unroll
        for (int g = 0; g < 8; ++g) { t0[g] = fmaxf(s[4 * g], s[4 * g + 1]); if (!HALF) t1[g] = fmaxf(s[4 * g + 2], s[4 * g + 3]); }
#pragma unroll
        for (int g = 0; g < 4; ++g) { t0[g] = fmaxf(t0[g], t0[g + 4]); if (!HALF) t1[g] = fmaxf(t1[g], t1[g + 4]); }
        float m0 = fmaxf(fmaxf(t0[0], t0[2]), fmaxf(t0[1], t0[3])), m1 = 0.f;
        if (!HALF) m1 = fmaxf(fmaxf(t1[0], t1[2]), fmaxf(t1[1], t1[3]));
        m0 = fmaxf(m0, __shfl_xor_sync(0xffffffffu, m0, 1));
        if (!HALF) m1 = fmaxf(m1, __shfl_xor_sync(0xffffffffu, m1, 1));
        m0 = fmaxf(m0, __shfl_xor_sync(0xffffffffu, m0, 2));
        if (!HALF) m1 = fmaxf(m1, __shfl_xor_sync(0xffffffffu, m1, 2));
        m0 *= CS; m1 *= CS;
        if (first) {
          mc0 = m0; mc1 = m1; l0 = 0.f; l1 = 0.f;
        } else {
          const float n0 = fmaxf(mc0, m0), n1 = fmaxf(mc1, m1);
          al0 = ex2(mc0 - n0);
          l0 *= al0; mc0 = n0;
          if (!HALF) { al1 = ex2(mc1 - n1); l1 *= al1; mc1 = n1; }
        }
      }
      float r0, r1 = 0.f;
      {
        float ra0 = 0.f, ra1 = 0.f, rb0 = 0.f, rb1 = 0.f;
#pragma unroll
        for (int g = 0; g < 8; ++g) {
          const float e0 = ex2(fmaf(s[4 * g], CS, -mc0)), e1 = ex2(fmaf(s[4 * g + 1], CS, -mc0));
          ra0 += e0; rb0 += e1;
          pn[2 * g] = pack_bf16(e0, e1);
          if (!HALF) {
            const float e2 = ex2(fmaf(s[4 * g + 2], CS, -mc1)), e3 = ex2(fmaf(s[4 * g + 3], CS, -mc1));
            ra1 += e2; rb1 += e3;
            pn[2 * g + 1] = pack_bf16(e2, e3);
          }
        }
        r0 = ra0 + rb0;
        if (!HALF) r1 = ra1 + rb1;
      }
      if (!upd && __any_sync(0xffffffffu, !(r0 <= 256.f) || !(r1 <= 256.f))) { upd = true; continue; }
      l0 += r0; l1 += r1;
      break;
    }
    return upd && !first;
  };
  auto epilogue = [&](int hh, float lf0, float lf1) {
    lf0 += __shfl_xor_sync(0xffffffffu, lf0, 1);
    if (!HALF) lf1 += __shfl_xor_sync(0xffffffffu, lf1, 1);
    lf0 += __shfl_xor_sync(0xffffffffu, lf0, 2);
    if (!HALF) lf1 += __shfl_xor_sync(0xffffffffu, lf1, 2);
    const float i0 = __frcp_rn(lf0), i1 = HALF ? 0.f : __frcp_rn(lf1);
    const int row = HALF ? 128 + A.warp * 8 + (lane >> 2) : wg * 64 + A.warp * 16 + (lane >> 2);
    __nv_bfloat16* dst = A.oscr + ((size_t)((A.bb * 64 + 2 * (h0 + hh)) * SQ + row)) * 64 + (lane & 3) * 8;
#pragma unroll
    for (int a = 0; a < 4; ++a) {
      uint4 v0;
      v0.x = pack_bf16(o[16 * a] * i0, o[16 * a + 1] * i0);
      v0.y = pack_bf16(o[16 * a + 4] * i0, o[16 * a + 5] * i0);
      v0.z = pack_bf16(o[16 * a + 8] * i0, o[16 * a + 9] * i0);
      v0.w = pack_bf16(o[16 * a + 12] * i0, o[16 * a + 13] * i0);
      *reinterpret_cast<uint4*>(dst + (a >> 1) * (SQ * 64) + (a & 1) * 32) = v0;
      if (!HALF) {
        uint4 v1;
        v1.x = pack_bf16(o[16 * a + 2] * i1, o[16 * a + 3] * i1);
        v1.y = pack_bf16(o[16 * a + 6] * i1, o[16 * a + 7] * i1);
        v1.z = pack_bf16(o[16 * a + 10] * i1, o[16 * a + 11] * i1);
        v1.w = pack_bf16(o[16 * a + 14] * i1, o[16 * a + 15] * i1);
        *reinterpret_cast<uint4*>(dst + (a >> 1) * (SQ * 64) + (a & 1) * 32 + 8 * 64) = v1;
      }
    }
  };

  float al0 = 1.f, al1 = 1.f;
  mbar_wait(sb + BAR_FULL + kc.slot * 8, kc.ph);
  issue_qk(0);
  wg_wait<0>();
  fence_regs(s);
  done_qk(0);
  softmax(true, p, al0, al1);
  mbar_wait(sb + BAR_FULL + kc.slot * 8, kc.ph);
  mbar_wait(sb + BAR_FULL + vc.slot * 8, vc.ph);
  auto step = [&](int n, uint32_t (&pc)[16], uint32_t (&pn)[16], bool last) {
    PROF2(n, 0);
    issue_qk(n + 1);
    PROF2(n, 1);
    issue_pv(n, pc);
    PROF2(n, 2);
    wg_wait<1>();
    fence_regs(s);
    PROF2(n, 3);
    done_qk(n + 1);
    Cursor vn = vc; vn.adv2();
    const bool kok = last || mbar_try(sb + BAR_FULL + kc.slot * 8, kc.ph);
    const bool vok = mbar_try(sb + BAR_FULL + vn.slot * 8, vn.ph);
    const bool head_end = (n & 7) == 7;
    const float lf0 = l0, lf1 = l1;
    const bool resc = softmax(head_end, pn, al0, al1);
    fence_regs(pn);
    PROF2(n, 4);
    wg_wait<0>();
    fence_regs(o);
    fence_regs(pc);
    PROF2(n, 5);
    release_ring(sb, vc.slot, 2 * n + 10 >= 2 * nblk && rank == 1, peer, elected);
    vc = vn;
    if (head_end) {
      epilogue(0, lf0, lf1);
    } else if (resc) {
#pragma unroll
      for (int g = 0; g < 16; ++g) {
        o[4 * g] *= al0; o[4 * g + 1] *= al0;
        if (!HALF) { o[4 * g + 2] *= al1; o[4 * g + 3] *= al1; }
      }
    }
    if (!kok) mbar_wait(sb + BAR_FULL + kc.slot * 8, kc.ph);
    if (!vok) mbar_wait(sb + BAR_FULL + vc.slot * 8, vc.ph);
    PROF2(n, 6);
  };
  for (int n = 0; n < nblk - 2; n += 2) {
    step(n, p, p2, false);
    step(n + 1, p2, p, false);
  }
  step(nblk - 2, p, p2, true);
  issue_pv(nblk - 1, p2);
  wg_wait<0>();
  fence_regs(o);
  release_ring(sb, vc.slot, rank == 1, peer, elected);
  epilogue(nh - 1, l0, l1);
  cur = kc;
}

__device__ __forceinline__ void consumer(const KParams& P, uint32_t sb, int wg, int blk, int b, int j, uint32_t rank,
                                         __nv_bfloat16* __restrict__ oscr, unsigned int* flags) {
  const int tid = threadIdx.x & 127;
  const int warp = tid >> 5, lane = tid & 31;
  const bool elected = tid == 0;
  const uint32_t peer = __shfl_sync(0xffffffffu, mapa(sb, rank ^ 1), 0);
  Cursor cur{0, 0};
  uint32_t xg = 0;

  const bool stag = STAGGER && (j & 1);
  const int nitems = stag ? 5 : 4;
  const AttnCtx A{sb, peer, rank, wg, warp, lane, blk * NBATCH + b, elected, oscr};
  unsigned int* myflag = flags + (blk * NBATCH + b) * 8 + 2 * j;
  auto publish = [&](unsigned int* f) {
    asm volatile("fence.proxy.async;" ::: "memory");
    __threadfence();
    bar_sync(2 + wg, 128);
    if (elected) asm volatile("red.release.gpu.global.add.u32 [%0], 1;" ::"l"(f) : "memory");
  };

  for (int item = 0; item <= nitems; ++item) {
    const bool ph2 = item == nitems;
    const int nk = ph2 ? 64 : 16;
    const int nh = ph2 ? 2 : item_heads(stag, item);
    PROF((ph2 ? 5 : item) * 4 + 0);
    {
      float a0[80], a1[28];
#pragma unroll
      for (int i = 0; i < 80; ++i) a0[i] = 0.f;
#pragma unroll
      for (int i = 0; i < 28; ++i) a1[i] = 0.f;
      const int rem_lim = 2 * nk - 9;
      uint32_t pslotA = 0, pslotB = 0, pxs = 0;
      auto rel_prev = [&](int ks) {
        const int off = 2 * (ks - 1);
        release_ring(sb, pslotA, off < rem_lim && rank == 0, peer, elected);
        release_ring(sb, pslotB, off + 1 < rem_lim && rank == 1, peer, elected);
        mbar_arrive_if(sb + BAR_XEMPTY + pxs * 8, ks - 1 < nk - 4 && elected);
      };
      if (nh == 2) {
        for (int ks = 0; ks < nk; ++ks) {
          const uint32_t sA = cur.slot, phA = cur.ph; cur.adv();
          const uint32_t sB = cur.slot, phB = cur.ph; cur.adv();
          const uint32_t xs = xg & 3;
          if (elected && wg == 0) PROF3(xg, 4);
          mbar_wait(sb + BAR_FULL + sA * 8, phA);
          mbar_wait(sb + BAR_FULL + sB * 8, phB);
          if (elected && wg == 0) PROF3(xg, 5);
          mbar_wait(sb + BAR_XFULL + xs * 8, (xg >> 2) & 1);
          if (elected && wg == 0) PROF3(xg, 6);
          const uint32_t aMain = sb + SM_RING + (wg < 2 ? sA : sB) * RSLOT + (wg & 1) * 8192;
          const uint32_t a3 = sb + SM_RING + sB * RSLOT + 8192;
          const uint32_t xb = sb + SM_XQ + xs * XSLOT;
          const uint64_t dA = make_desc(aMain, 0, 1024), dA3 = make_desc(a3, 0, 1024);
          const uint64_t dB = make_desc(xb, 0, 1024), dB3 = make_desc(xb + wg * 7168, 0, 1024);
          wg_fence();
#pragma unroll
          for (int kk = 0; kk < 4; ++kk) {
            const int sd = (ks | kk) != 0;
            wgmma_ss_n160<1, 0>(a0, dA + kk * 128, dB + kk * 2, sd);
            wgmma_ss_n56<1, 0>(a1, dA3 + kk * 128, dB3 + kk * 2, sd);
          }
          wg_commit();
          if (ks > 0) { wg_wait<1>(); rel_prev(ks); }
          pslotA = sA; pslotB = sB; pxs = xs;
          ++xg;
        }
        wg_wait<0>();
        fence_regs(a0); fence_regs(a1);
      } else if (wg < 2) {
        for (int ks = 0; ks < nk; ++ks) {
          const uint32_t sA = cur.slot, phA = cur.ph; cur.adv();
          const uint32_t sB = cur.slot, phB = cur.ph; cur.adv();
          const uint32_t xs = xg & 3;
          mbar_wait(sb + BAR_FULL + sA * 8, phA);
          mbar_wait(sb + BAR_FULL + sB * 8, phB);
          mbar_wait(sb + BAR_XFULL + xs * 8, (xg >> 2) & 1);
          const uint64_t dA = make_desc(sb + SM_RING + (wg == 0 ? sA : sB) * RSLOT, 0, 1024);
          const uint64_t dB = make_desc(sb + SM_XQ + xs * XSLOT, 0, 1024);
          wg_fence();
#pragma unroll
          for (int kk = 0; kk < 4; ++kk) wgmma_ss_n160<1, 0>(a0, dA + kk * 128, dB + kk * 2, (ks | kk) != 0);
          wg_commit();
          if (ks > 0) { wg_wait<1>(); rel_prev(ks); }
          pslotA = sA; pslotB = sB; pxs = xs;
          ++xg;
        }
        wg_wait<0>();
        fence_regs(a0);
      } else {
        for (int ks = 0; ks < nk; ++ks) {
          const uint32_t sA = cur.slot, phA = cur.ph; cur.adv();
          const uint32_t sB = cur.slot, phB = cur.ph; cur.adv();
          const uint32_t xs = xg & 3;
          if (ks > 0) rel_prev(ks);
          mbar_wait(sb + BAR_FULL + sA * 8, phA);
          mbar_wait(sb + BAR_FULL + sB * 8, phB);
          mbar_wait(sb + BAR_XFULL + xs * 8, (xg >> 2) & 1);
          pslotA = sA; pslotB = sB; pxs = xs;
          ++xg;
        }
      }
      release_ring(sb, pslotA, false, peer, elected);
      release_ring(sb, pslotB, false, peer, elected);
      PROF((ph2 ? 5 : item) * 4 + 1);
      bar_sync(1, 384);
      const int mi = lane >> 3, i8 = lane & 7;
      const uint32_t lane_off = (8 * (mi >> 1) + i8) * 128 + (((2 * warp + (mi & 1)) ^ i8) << 4);
      if (nh == 2 || wg < 2) store_T<20>(a0, sb + SM_XQ + wg * XSLOT + lane_off, 20);
      if (nh == 2) {
        store_T<7>(a1, sb + SM_XQ + 3 * XSLOT + wg * 7168 + lane_off, wg == 2 ? 6 : 7);
      } else {
        mbar_arrive_if(sb + BAR_XEMPTY + 2 * 8, elected);
        mbar_arrive_if(sb + BAR_XEMPTY + 3 * 8, elected);
      }
      asm volatile("fence.proxy.async.shared::cta;" ::: "memory");
      bar_sync(1, 384);
    }
    PROF((ph2 ? 5 : item) * 4 + 2);
    if (ph2) {
      if (wg == 0 && elected) {
#pragma unroll
        for (int mt = 0; mt < 4; ++mt)
          tma_store_2d(&P.out, sb + SM_XQ + mt * XSLOT, blk * 1024 + 256 * j + 64 * mt, SQ * b);
        asm volatile("cp.async.bulk.commit_group;" ::: "memory");
        asm volatile("cp.async.bulk.wait_group 0;" ::: "memory");
      }
      PROF(5 * 4 + 3);
      break;
    }
    if (item == nitems - 1) publish(myflag);
    const int h0 = 8 * j + item_head0(stag, item);
    if (wg == 2) attention<true>(A, cur, item, h0, nh);
    else attention<false>(A, cur, item, h0, nh);
    PROF(item * 4 + 3);
    if (item == nitems - 1) publish(myflag + 1);
  }
}

__global__ void __cluster_dims__(2, 1, 1) __launch_bounds__(NTHREADS, 1)
fused_mha_kernel(const __grid_constant__ KParams P, __nv_bfloat16* __restrict__ oscr, unsigned int* flags) {
  extern __shared__ uint8_t smem_raw[];
  const uint32_t sb = __shfl_sync(0xffffffffu, (smem_u32(smem_raw) + 1023) & ~1023u, 0);
  const int wg = __shfl_sync(0xffffffffu, threadIdx.x >> 7, 0);
  uint32_t rank;
  asm("mov.u32 %0, %%cluster_ctarank;" : "=r"(rank));
  const int c = blockIdx.x >> 1;
  const int blk = c >> 5, pr = (c & 31) >> 2, j = c & 3;
  const int b = 2 * pr + (int)rank;
  if (threadIdx.x == 0) {
    for (int i = 0; i < NRING; ++i) { mbar_init(sb + BAR_FULL + i * 8, 1); mbar_init(sb + BAR_EMPTY + i * 8, 3); mbar_init(sb + BAR_PEMPTY + i * 8, 3); }
    for (int i = 0; i < 4; ++i) { mbar_init(sb + BAR_XFULL + i * 8, 1); mbar_init(sb + BAR_XEMPTY + i * 8, 3); }
    asm volatile("st.volatile.shared.u32 [%0], %1;" ::"r"(sb + SM_ABORT), "r"(0u) : "memory");
    asm volatile("fence.mbarrier_init.release.cluster;" ::: "memory");
  }
  __syncthreads();
  cluster_sync_all();
  if (wg == 3) {
    asm volatile("setmaxnreg.dec.sync.aligned.u32 32;");
    const int warp = __shfl_sync(0xffffffffu, threadIdx.x >> 5, 0);
    if (warp == 12) producer_ring(P, sb, blk, b, j, rank);
    else if (warp == 13) producer_x(P, sb, blk, b, j, flags);
    cluster_sync_all();
  } else {
    asm volatile("setmaxnreg.inc.sync.aligned.u32 160;");
    consumer(P, sb, wg, blk, b, j, rank, oscr, flags);
    cluster_sync_all();
  }
}

typedef CUresult (*EncodeFn)(CUtensorMap*, CUtensorMapDataType, cuuint32_t, void*, const cuuint64_t*, const cuuint64_t*,
                             const cuuint32_t*, const cuuint32_t*, CUtensorMapInterleave, CUtensorMapSwizzle,
                             CUtensorMapL2promotion, CUtensorMapFloatOOBfill);

bool encode(EncodeFn fn, CUtensorMap* tm, const void* base, int rank, const cuuint64_t* dims, const cuuint64_t* strides,
            const cuuint32_t* box) {
  cuuint32_t es[5] = {1, 1, 1, 1, 1};
  CUresult r = fn(tm, CU_TENSOR_MAP_DATA_TYPE_BFLOAT16, rank, const_cast<void*>(base), dims, strides, box, es,
                  CU_TENSOR_MAP_INTERLEAVE_NONE, CU_TENSOR_MAP_SWIZZLE_128B, CU_TENSOR_MAP_L2_PROMOTION_L2_256B,
                  CU_TENSOR_MAP_FLOAT_OOB_FILL_NONE);
  return r == CUDA_SUCCESS;
}

}

extern "C" void kernel_launch(void* const* d_in, const int* in_sizes, int n_in, void* d_out, int out_size) {
  (void)in_sizes; (void)n_in; (void)out_size;
  static KParams P;
  static bool ready = false;
  static __nv_bfloat16* oscr = nullptr;
  static unsigned int* flags = nullptr;
  static const void* last_ptrs[11] = {};
  bool same = ready;
  for (int i = 0; i < 10; ++i) same = same && last_ptrs[i] == d_in[i];
  same = same && last_ptrs[10] == d_out;
  if (!same) {
    void* fnp = nullptr;
    cudaDriverEntryPointQueryResult qr;
    cudaGetDriverEntryPoint("cuTensorMapEncodeTiled", &fnp, cudaEnableDefault, &qr);
    EncodeFn fn = (EncodeFn)fnp;
    cudaGetSymbolAddress((void**)&oscr, g_o);
    cudaGetSymbolAddress((void**)&flags, g_flags);
    bool ok = fn != nullptr;
    for (int blk = 0; blk < 2 && ok; ++blk) {
      const void* x = d_in[5 * blk + 0]; const void* k = d_in[5 * blk + 1]; const void* v = d_in[5 * blk + 2];
      const void* wq = d_in[5 * blk + 3]; const void* wo = d_in[5 * blk + 4];
      { cuuint64_t d[2] = {1024, 2560}, s[1] = {2048}; cuuint32_t bx[2] = {64, 160}; ok = ok && encode(fn, &P.x[blk], x, 2, d, s, bx); }
      { cuuint64_t d[2] = {4096, 1024}, s[1] = {8192}; cuuint32_t bx[2] = {64, 64}; ok = ok && encode(fn, &P.wq[blk], wq, 2, d, s, bx); }
      { cuuint64_t d[2] = {128, 262144}, s[1] = {256}; cuuint32_t bx[2] = {64, 64};
        ok = ok && encode(fn, &P.k[blk], k, 2, d, s, bx); ok = ok && encode(fn, &P.v[blk], v, 2, d, s, bx); }
      { cuuint64_t d[5] = {1024, 2, 4, 4, 128}, s[4] = {2048, 2048 * 8, 2048 * 2, 2048 * 32}; cuuint32_t bx[5] = {64, 2, 4, 4, 2};
        ok = ok && encode(fn, &P.wo[blk], wo, 5, d, s, bx); }
    }
    { cuuint64_t d[2] = {64, 32 * 64 * 160}, s[1] = {128}; cuuint32_t bx[2] = {64, 160}; ok = ok && encode(fn, &P.o, oscr, 2, d, s, bx); }
    { cuuint64_t d[2] = {2048, 2560}, s[1] = {4096}; cuuint32_t bx[2] = {64, 160}; ok = ok && encode(fn, &P.out, d_out, 2, d, s, bx); }
    if (!ok) { ready = false; return; }
    cudaFuncSetAttribute(fused_mha_kernel, cudaFuncAttributeMaxDynamicSharedMemorySize, SMEM_BYTES);
    for (int i = 0; i < 10; ++i) last_ptrs[i] = d_in[i];
    last_ptrs[10] = d_out;
    ready = true;
  }
  fused_mha_kernel<<<NCTA, NTHREADS, SMEM_BYTES, cudaStreamPerThread>>>(P, oscr, flags);
}
```

```cpp
#include <cuda_runtime.h>
#include <cuda_bf16.h>
#include <cuda.h>
#include <stdint.h>

namespace {

constexpr int SQ = 160, NH = 32, SK = 512, DH = 128, NBATCH = 16;
constexpr int XSLOT = 20480;
constexpr int RSLOT = 16384;
constexpr int NRING = 9;
constexpr int SM_XQ = 0;
constexpr int SM_RING = 4 * XSLOT;
constexpr int SM_BAR = SM_RING + NRING * RSLOT;
constexpr int BAR_FULL = SM_BAR;
constexpr int BAR_EMPTY = SM_BAR + 72;
constexpr int BAR_PEMPTY = SM_BAR + 144;
constexpr int BAR_XFULL = SM_BAR + 216;
constexpr int BAR_XEMPTY = SM_BAR + 248;
constexpr int BAR_OSTAGE = SM_BAR + 280;
constexpr int BAR_KVDONE = SM_BAR + 304;
constexpr int SM_ABORT = SM_BAR + 1016;
constexpr int SMEM_BYTES = SM_BAR + 1024 + 1024;
constexpr int NTHREADS = 512;
constexpr int NCTA = 128;
constexpr uint32_t SPIN_LIMIT = 1u << 22;

struct __align__(64) KParams {
  CUtensorMap x[2], wq[2], k[2], v[2], wo[2], out;
};

__device__ __nv_bfloat16 g_o[2 * NBATCH * SQ * NH * DH];
__device__ unsigned int g_flags[256];

__device__ __forceinline__ uint32_t smem_u32(const void* p) { return (uint32_t)__cvta_generic_to_shared(p); }
__device__ __forceinline__ void mbar_init(uint32_t bar, uint32_t cnt) {
  asm volatile("mbarrier.init.shared::cta.b64 [%0], %1;" ::"r"(bar), "r"(cnt));
}
__device__ __forceinline__ void mbar_expect_tx(uint32_t bar, uint32_t bytes) {
  asm volatile("mbarrier.arrive.expect_tx.shared::cta.b64 _, [%0], %1;" ::"r"(bar), "r"(bytes) : "memory");
}
__device__ __forceinline__ void mbar_arrive_if(uint32_t bar, bool pred) {
  asm volatile("{\n.reg .pred p;\nsetp.ne.b32 p, %1, 0;\n@p mbarrier.arrive.shared::cta.b64 _, [%0];\n}" ::"r"(bar), "r"((int)pred) : "memory");
}
__device__ __forceinline__ void mbar_arrive_remote_if(uint32_t remote_bar, bool pred) {
  asm volatile("{\n.reg .pred p;\nsetp.ne.b32 p, %1, 0;\n@p mbarrier.arrive.shared::cluster.b64 _, [%0];\n}" ::"r"(remote_bar), "r"((int)pred) : "memory");
}
__device__ __forceinline__ uint32_t mapa(uint32_t addr, uint32_t cta) {
  uint32_t r;
  asm("mapa.shared::cluster.u32 %0, %1, %2;" : "=r"(r) : "r"(addr), "r"(cta));
  return r;
}
__device__ __forceinline__ bool spin_giveup(uint32_t abort_addr, uint32_t& spins) {
  uint32_t ab;
  asm volatile("ld.volatile.shared.u32 %0, [%1];" : "=r"(ab) : "r"(abort_addr) : "memory");
  if (++spins > SPIN_LIMIT) {
    asm volatile("st.volatile.shared.u32 [%0], %1;" ::"r"(abort_addr), "r"(1u) : "memory");
    ab = 1;
  }
  return ab != 0;
}
__device__ __forceinline__ void mbar_wait(uint32_t bar, uint32_t parity) {
  uint32_t ok, spins = 0;
  while (true) {
    asm volatile("{\n.reg .pred p;\nmbarrier.try_wait.parity.shared::cta.b64 p, [%1], %2;\nselp.u32 %0, 1, 0, p;\n}"
                 : "=r"(ok) : "r"(bar), "r"(parity) : "memory");
    if (ok) break;
    if (spin_giveup((bar & ~1023u) + 1016u, spins)) break;
  }
}
__device__ __forceinline__ void tma_2d(uint32_t dst, const CUtensorMap* tm, uint32_t bar, int c0, int c1) {
  asm volatile("cp.async.bulk.tensor.2d.shared::cluster.global.mbarrier::complete_tx::bytes [%0], [%1, {%3, %4}], [%2];"
               ::"r"(dst), "l"(tm), "r"(bar), "r"(c0), "r"(c1) : "memory");
}
__device__ __forceinline__ void tma_2d_hint(uint32_t dst, const CUtensorMap* tm, uint32_t bar, int c0, int c1, uint64_t pol) {
  asm volatile("cp.async.bulk.tensor.2d.shared::cluster.global.mbarrier::complete_tx::bytes.L2::cache_hint [%0], [%1, {%3, %4}], [%2], %5;"
               ::"r"(dst), "l"(tm), "r"(bar), "r"(c0), "r"(c1), "l"(pol) : "memory");
}
__device__ __forceinline__ void tma_2d_mc(uint32_t dst, const CUtensorMap* tm, uint32_t bar, int c0, int c1, uint16_t mask) {
  asm volatile("cp.async.bulk.tensor.2d.shared::cluster.global.mbarrier::complete_tx::bytes.multicast::cluster [%0], [%1, {%3, %4}], [%2], %5;"
               ::"r"(dst), "l"(tm), "r"(bar), "r"(c0), "r"(c1), "h"(mask) : "memory");
}
__device__ __forceinline__ void tma_store_2d(const CUtensorMap* tm, uint32_t src, int c0, int c1) {
  asm volatile("cp.async.bulk.tensor.2d.global.shared::cta.bulk_group [%0, {%2, %3}], [%1];"
               ::"l"(tm), "r"(src), "r"(c0), "r"(c1) : "memory");
}
__device__ __forceinline__ void bulk_load(uint32_t dst, const void* src, uint32_t bytes, uint32_t bar) {
  asm volatile("cp.async.bulk.shared::cluster.global.mbarrier::complete_tx::bytes [%0], [%1], %2, [%3];"
               ::"r"(dst), "l"(src), "r"(bytes), "r"(bar) : "memory");
}
__device__ __forceinline__ void bulk_store(void* dst, uint32_t src, uint32_t bytes) {
  uint64_t pol;
  asm volatile("createpolicy.fractional.L2::evict_first.b64 %0, 1.0;" : "=l"(pol));
  asm volatile("cp.async.bulk.global.shared::cta.bulk_group.L2::cache_hint [%0], [%1], %2, %3;" ::"l"(dst), "r"(src), "r"(bytes), "l"(pol) : "memory");
}
__device__ __forceinline__ void stsm_x4(uint32_t addr, uint32_t r0, uint32_t r1, uint32_t r2, uint32_t r3) {
  asm volatile("stmatrix.sync.aligned.m8n8.x4.shared.b16 [%0], {%1, %2, %3, %4};" ::"r"(addr), "r"(r0), "r"(r1), "r"(r2), "r"(r3) : "memory");
}
__device__ __forceinline__ void wg_fence() { asm volatile("wgmma.fence.sync.aligned;" ::: "memory"); }
__device__ __forceinline__ void wg_commit() { asm volatile("wgmma.commit_group.sync.aligned;" ::: "memory"); }
template <int N> __device__ __forceinline__ void wg_wait() { asm volatile("wgmma.wait_group.sync.aligned %0;" ::"n"(N) : "memory"); }
template <int N> __device__ __forceinline__ void fence_regs(float (&a)[N]) {
#pragma unroll
  for (int i = 0; i < N; i++) asm volatile("" : "+f"(a[i])::"memory");
}
template <int N> __device__ __forceinline__ void fence_regs(uint32_t (&a)[N]) {
#pragma unroll
  for (int i = 0; i < N; i++) asm volatile("" : "+r"(a[i])::"memory");
}
__device__ __forceinline__ uint64_t make_desc(uint32_t addr, uint32_t lbo, uint32_t sbo) {
  uint32_t lo = ((addr & 0x3FFFF) >> 4) | ((lbo >> 4) << 16);
  uint32_t hi = (sbo >> 4) | (1u << 30);
  return ((uint64_t)hi << 32) | lo;
}
__device__ __forceinline__ uint32_t pack_bf16(float lo, float hi) {
  uint32_t r;
  asm("cvt.rn.bf16x2.f32 %0, %1, %2;" : "=r"(r) : "f"(hi), "f"(lo));
  return r;
}
__device__ __forceinline__ float rcp_fast(float x) {
  float y;
  asm("rcp.approx.ftz.f32 %0, %1;" : "=f"(y) : "f"(x));
  return y;
}
__device__ __forceinline__ float ex2(float x) {
  float y;
  asm("ex2.approx.ftz.f32 %0, %1;" : "=f"(y) : "f"(x));
  return y;
}
__device__ __forceinline__ void stsm_x4_t(uint32_t addr, uint32_t r0, uint32_t r1, uint32_t r2, uint32_t r3) {
  asm volatile("stmatrix.sync.aligned.m8n8.x4.trans.shared.b16 [%0], {%1, %2, %3, %4};" ::"r"(addr), "r"(r0), "r"(r1), "r"(r2), "r"(r3) : "memory");
}
__device__ __forceinline__ void bar_sync(int id, int n) { asm volatile("bar.sync %0, %1;" ::"r"(id), "r"(n) : "memory"); }

template <int TA, int TB>
__device__ __forceinline__ void wgmma_ss_n160(float (&d)[80], uint64_t da, uint64_t db, int sd) {
  asm volatile("{\n.reg .pred p;\nsetp.ne.b32 p, %82, 0;\n"
    "wgmma.mma_async.sync.aligned.m64n160k16.f32.bf16.bf16 {"
    "%0, %1, %2, %3, %4, %5, %6, %7, %8, %9, %10, %11, %12, %13, %14, %15, %16, %17, %18, %19, %20, %21, %22, %23, %24, %25, %26, %27, %28, %29, %30, %31, "
    "%32, %33, %34, %35, %36, %37, %38, %39, %40, %41, %42, %43, %44, %45, %46, %47, %48, %49, %50, %51, %52, %53, %54, %55, %56, %57, %58, %59, %60, %61, "
    "%62, %63, %64, %65, %66, %67, %68, %69, %70, %71, %72, %73, %74, %75, %76, %77, %78, %79"
    "}, %80, %81, p, 1, 1, %83, %84;\n}\n"
    : "+f"(d[0]), "+f"(d[1]), "+f"(d[2]), "+f"(d[3]), "+f"(d[4]), "+f"(d[5]), "+f"(d[6]), "+f"(d[7]), "+f"(d[8]), "+f"(d[9]), "+f"(d[10]), "+f"(d[11]),
      "+f"(d[12]), "+f"(d[13]), "+f"(d[14]), "+f"(d[15]), "+f"(d[16]), "+f"(d[17]), "+f"(d[18]), "+f"(d[19]), "+f"(d[20]), "+f"(d[21]), "+f"(d[22]),
      "+f"(d[23]), "+f"(d[24]), "+f"(d[25]), "+f"(d[26]), "+f"(d[27]), "+f"(d[28]), "+f"(d[29]), "+f"(d[30]), "+f"(d[31]), "+f"(d[32]), "+f"(d[33]),
      "+f"(d[34]), "+f"(d[35]), "+f"(d[36]), "+f"(d[37]), "+f"(d[38]), "+f"(d[39]), "+f"(d[40]), "+f"(d[41]), "+f"(d[42]), "+f"(d[43]), "+f"(d[44]),
      "+f"(d[45]), "+f"(d[46]), "+f"(d[47]), "+f"(d[48]), "+f"(d[49]), "+f"(d[50]), "+f"(d[51]), "+f"(d[52]), "+f"(d[53]), "+f"(d[54]), "+f"(d[55]),
      "+f"(d[56]), "+f"(d[57]), "+f"(d[58]), "+f"(d[59]), "+f"(d[60]), "+f"(d[61]), "+f"(d[62]), "+f"(d[63]), "+f"(d[64]), "+f"(d[65]), "+f"(d[66]),
      "+f"(d[67]), "+f"(d[68]), "+f"(d[69]), "+f"(d[70]), "+f"(d[71]), "+f"(d[72]), "+f"(d[73]), "+f"(d[74]), "+f"(d[75]), "+f"(d[76]), "+f"(d[77]),
      "+f"(d[78]), "+f"(d[79])
    : "l"(da), "l"(db), "r"(sd), "n"(TA), "n"(TB));
}
template <int TA, int TB>
__device__ __forceinline__ void wgmma_ss_n80(float (&d)[40], uint64_t da, uint64_t db, int sd) {
  asm volatile("{\n.reg .pred p;\nsetp.ne.b32 p, %42, 0;\n"
    "wgmma.mma_async.sync.aligned.m64n80k16.f32.bf16.bf16 {"
    "%0, %1, %2, %3, %4, %5, %6, %7, %8, %9, %10, %11, %12, %13, %14, %15, %16, %17, %18, %19, %20, %21, %22, %23, %24, %25, %26, %27, %28, %29, %30, %31, "
    "%32, %33, %34, %35, %36, %37, %38, %39"
    "}, %40, %41, p, 1, 1, %43, %44;\n}\n"
    : "+f"(d[0]), "+f"(d[1]), "+f"(d[2]), "+f"(d[3]), "+f"(d[4]), "+f"(d[5]), "+f"(d[6]), "+f"(d[7]), "+f"(d[8]), "+f"(d[9]), "+f"(d[10]), "+f"(d[11]),
      "+f"(d[12]), "+f"(d[13]), "+f"(d[14]), "+f"(d[15]), "+f"(d[16]), "+f"(d[17]), "+f"(d[18]), "+f"(d[19]), "+f"(d[20]), "+f"(d[21]), "+f"(d[22]),
      "+f"(d[23]), "+f"(d[24]), "+f"(d[25]), "+f"(d[26]), "+f"(d[27]), "+f"(d[28]), "+f"(d[29]), "+f"(d[30]), "+f"(d[31]), "+f"(d[32]), "+f"(d[33]),
      "+f"(d[34]), "+f"(d[35]), "+f"(d[36]), "+f"(d[37]), "+f"(d[38]), "+f"(d[39])
    : "l"(da), "l"(db), "r"(sd), "n"(TA), "n"(TB));
}
template <int TA, int TB>
__device__ __forceinline__ void wgmma_ss_n64(float (&d)[32], uint64_t da, uint64_t db, int sd) {
  asm volatile("{\n.reg .pred p;\nsetp.ne.b32 p, %34, 0;\n"
    "wgmma.mma_async.sync.aligned.m64n64k16.f32.bf16.bf16 {"
    "%0, %1, %2, %3, %4, %5, %6, %7, %8, %9, %10, %11, %12, %13, %14, %15, %16, %17, %18, %19, %20, %21, %22, %23, %24, %25, %26, %27, %28, %29, %30, %31"
    "}, %32, %33, p, 1, 1, %35, %36;\n}\n"
    : "+f"(d[0]), "+f"(d[1]), "+f"(d[2]), "+f"(d[3]), "+f"(d[4]), "+f"(d[5]), "+f"(d[6]), "+f"(d[7]), "+f"(d[8]), "+f"(d[9]), "+f"(d[10]), "+f"(d[11]),
      "+f"(d[12]), "+f"(d[13]), "+f"(d[14]), "+f"(d[15]), "+f"(d[16]), "+f"(d[17]), "+f"(d[18]), "+f"(d[19]), "+f"(d[20]), "+f"(d[21]), "+f"(d[22]),
      "+f"(d[23]), "+f"(d[24]), "+f"(d[25]), "+f"(d[26]), "+f"(d[27]), "+f"(d[28]), "+f"(d[29]), "+f"(d[30]), "+f"(d[31])
    : "l"(da), "l"(db), "r"(sd), "n"(TA), "n"(TB));
}
template <int TB>
__device__ __forceinline__ void wgmma_rs_n128(float (&d)[64], uint32_t a0, uint32_t a1, uint32_t a2, uint32_t a3, uint64_t db, int sd) {
  asm volatile("{\n.reg .pred p;\nsetp.ne.b32 p, %69, 0;\n"
    "wgmma.mma_async.sync.aligned.m64n128k16.f32.bf16.bf16 {"
    "%0, %1, %2, %3, %4, %5, %6, %7, %8, %9, %10, %11, %12, %13, %14, %15, %16, %17, %18, %19, %20, %21, %22, %23, %24, %25, %26, %27, %28, %29, %30, %31, "
    "%32, %33, %34, %35, %36, %37, %38, %39, %40, %41, %42, %43, %44, %45, %46, %47, %48, %49, %50, %51, %52, %53, %54, %55, %56, %57, %58, %59, %60, %61, "
    "%62, %63"
    "}, {%64, %65, %66, %67}, %68, p, 1, 1, %70;\n}\n"
    : "+f"(d[0]), "+f"(d[1]), "+f"(d[2]), "+f"(d[3]), "+f"(d[4]), "+f"(d[5]), "+f"(d[6]), "+f"(d[7]), "+f"(d[8]), "+f"(d[9]), "+f"(d[10]), "+f"(d[11]),
      "+f"(d[12]), "+f"(d[13]), "+f"(d[14]), "+f"(d[15]), "+f"(d[16]), "+f"(d[17]), "+f"(d[18]), "+f"(d[19]), "+f"(d[20]), "+f"(d[21]), "+f"(d[22]),
      "+f"(d[23]), "+f"(d[24]), "+f"(d[25]), "+f"(d[26]), "+f"(d[27]), "+f"(d[28]), "+f"(d[29]), "+f"(d[30]), "+f"(d[31]), "+f"(d[32]), "+f"(d[33]),
      "+f"(d[34]), "+f"(d[35]), "+f"(d[36]), "+f"(d[37]), "+f"(d[38]), "+f"(d[39]), "+f"(d[40]), "+f"(d[41]), "+f"(d[42]), "+f"(d[43]), "+f"(d[44]),
      "+f"(d[45]), "+f"(d[46]), "+f"(d[47]), "+f"(d[48]), "+f"(d[49]), "+f"(d[50]), "+f"(d[51]), "+f"(d[52]), "+f"(d[53]), "+f"(d[54]), "+f"(d[55]),
      "+f"(d[56]), "+f"(d[57]), "+f"(d[58]), "+f"(d[59]), "+f"(d[60]), "+f"(d[61]), "+f"(d[62]), "+f"(d[63])
    : "r"(a0), "r"(a1), "r"(a2), "r"(a3), "l"(db), "r"(sd), "n"(TB));
}


struct PCursor {
  uint32_t slot, eph, pbits;
  __device__ __forceinline__ void adv() { if (++slot == NRING) { slot = 0; eph ^= 1; pbits |= 0x80000000u; } }
};

__device__ __forceinline__ int item_heads(bool stag, int item) { return (stag && (item == 0 || item == 4)) ? 1 : 2; }
__device__ __forceinline__ int item_head0(bool stag, int item) { return stag ? (item == 0 ? 0 : 2 * item - 1) : 2 * item; }
__device__ __forceinline__ int ph2_chunk(int kk) { return 4 * (4 * ((kk >> 2) & 3) + (kk >> 4)) + (kk & 3); }

__device__ __forceinline__ bool elect_one() {
  uint32_t pred;
  asm volatile("{\n.reg .pred p;\nelect.sync _|p, 0xffffffff;\nselp.u32 %0, 1, 0, p;\n}" : "=r"(pred));
  return pred != 0;
}

template <int MODE>
__device__ __forceinline__ void produce_w(const KParams& P, uint32_t sb, PCursor& c, int blk, uint32_t rank, int col0, int ks) {
#pragma unroll
  for (int h = 0; h < 2; ++h) {
    mbar_wait(sb + BAR_EMPTY + c.slot * 8, c.eph);
    const uint32_t fb = sb + BAR_FULL + c.slot * 8;
    if (h == (int)rank) {
      if (c.pbits >> 31) {
        mbar_wait(sb + BAR_PEMPTY + c.slot * 8, (c.pbits >> c.slot) & 1);
        c.pbits ^= 1u << c.slot;
      }
      const uint32_t dst = sb + SM_RING + c.slot * RSLOT;
      if (elect_one()) {
        mbar_expect_tx(fb, MODE == 1 ? 8192 : RSLOT);
        if (MODE == 0) {
          tma_2d_mc(dst, &P.wq[blk], fb, col0 + 128 * h, 64 * ks, 3);
          tma_2d_mc(dst + 8192, &P.wq[blk], fb, col0 + 128 * h + 64, 64 * ks, 3);
        } else if (MODE == 1) {
          tma_2d_mc(dst, &P.wq[blk], fb, col0 + 64 * h, 64 * ks, 3);
        } else {
          tma_2d_mc(dst, &P.wo[blk], fb, col0 + 128 * h, 64 * ks, 3);
          tma_2d_mc(dst + 8192, &P.wo[blk], fb, col0 + 128 * h + 64, 64 * ks, 3);
        }
      }
    } else {
      if (elect_one()) mbar_expect_tx(fb, MODE == 1 ? 8192 : RSLOT);
    }
    __syncwarp();
    c.adv();
  }
}

__device__ __forceinline__ void producer_ring(const KParams& P, uint32_t sb, int blk, int b, int j, uint32_t rank) {
  uint64_t pol_first;
  asm volatile("createpolicy.fractional.L2::evict_first.b64 %0, 1.0;" : "=l"(pol_first));
  PCursor c{0, 1, 0};
  const bool stag = (j & 1) != 0;
  const int nitems = stag ? 5 : 4;
#pragma unroll 1
  for (int item = 0; item < nitems; ++item) {
    const int nh = item_heads(stag, item), h0 = 8 * j + item_head0(stag, item);
    if (nh == 2) {
#pragma unroll 1
      for (int ks = 0; ks < 16; ++ks) produce_w<0>(P, sb, c, blk, rank, 128 * h0, ks);
    } else {
#pragma unroll 1
      for (int ks = 0; ks < 16; ++ks) produce_w<1>(P, sb, c, blk, rank, 128 * h0, ks);
    }
    int row = (b * NH + h0) * SK;
#pragma unroll 1
    for (int n = 0; n < 8 * nh; ++n, row += 64) {
#pragma unroll
      for (int kv = 0; kv < 2; ++kv) {
        mbar_wait(sb + BAR_EMPTY + c.slot * 8, c.eph);
        const uint32_t fb = sb + BAR_FULL + c.slot * 8;
        const uint32_t dst = sb + SM_RING + c.slot * RSLOT;
        const CUtensorMap* tm = kv == 0 ? &P.k[blk] : &P.v[blk];
        if (elect_one()) {
          mbar_expect_tx(fb, RSLOT);
          tma_2d_hint(dst, tm, fb, 0, row, pol_first);
          tma_2d_hint(dst + 8192, tm, fb, 64, row, pol_first);
        }
        __syncwarp();
        c.adv();
      }
    }
  }
#pragma unroll 1
  for (int kk = 0; kk < 64; ++kk) produce_w<2>(P, sb, c, blk, rank, 256 * j, ph2_chunk(kk));
}

__device__ __forceinline__ void producer_x(const KParams& P, uint32_t sb, int blk, int b, int j, const unsigned int* flags,
                                           const __nv_bfloat16* oscr) {
  const unsigned int* fl = flags + (blk * NBATCH + b) * 8;
  unsigned int fbase;
  asm volatile("ld.relaxed.gpu.global.u32 %0, [%1];" : "=r"(fbase) : "l"(fl + 2 * j) : "memory");
  const int n1 = ((j & 1) ? 5 : 4) * 16;
#pragma unroll 1
  for (int xg = 0; xg < n1 + 64; ++xg) {
    const uint32_t xs = xg & 3;
    const int kk = xg - n1;
    if (kk >= 0 && (kk & 3) == 0 && ((kk >> 4) == 0 || (kk >> 4) == 3)) {
      const unsigned int* fp = fl + 2 * ((kk >> 2) & 3) + ((kk >> 4) == 3);
      uint32_t spins = 0;
      while (true) {
        unsigned int v;
        asm volatile("ld.acquire.gpu.global.u32 %0, [%1];" : "=r"(v) : "l"(fp) : "memory");
        if (v - fbase >= 3u) break;
        if (spin_giveup(sb + SM_ABORT, spins)) break;
      }
      asm volatile("fence.proxy.async;" ::: "memory");
    }
    mbar_wait(sb + BAR_XEMPTY + xs * 8, ((xg >> 2) & 1) ^ 1);
    const uint32_t xb = sb + BAR_XFULL + xs * 8;
    if (elect_one()) {
      mbar_expect_tx(xb, XSLOT);
      if (kk >= 0) bulk_load(sb + SM_XQ + xs * XSLOT, reinterpret_cast<const char*>(oscr) + (size_t)((blk * NBATCH + b) * 64 + ph2_chunk(kk)) * XSLOT, XSLOT, xb);
      else tma_2d(sb + SM_XQ + xs * XSLOT, &P.x[blk], xb, 64 * (xg & 15), SQ * b);
    }
    __syncwarp();
  }
}

__device__ __forceinline__ void store_warp(uint32_t sb, uint32_t peer, uint32_t rank, int blk, int b, int j, unsigned int* flags,
                                           __nv_bfloat16* oscr) {
  if ((threadIdx.x & 31) != 0) return;
  const bool stag = (j & 1) != 0;
  const int nitems = stag ? 5 : 4;
  unsigned int* myflag = flags + (blk * NBATCH + b) * 8 + 2 * j;
  uint32_t ph = 0, use = 0;
#pragma unroll 1
  for (int item = 0; item < nitems; ++item) {
    const int nh = item_heads(stag, item), h0 = 8 * j + item_head0(stag, item);
    use += 32 + 16 * nh;
#pragma unroll 1
    for (int hh = 0; hh < nh; ++hh, ph ^= 1) {
      const bool ring = hh == nh - 1;
      char* dst = reinterpret_cast<char*>(oscr) + (size_t)((blk * NBATCH + b) * 64 + 2 * (h0 + hh)) * XSLOT;
#pragma unroll 1
      for (int w = 0; w < 3; ++w) {
        const uint32_t slot = (use - (w == 0 ? 2 : w == 1 ? 3 : 1)) % NRING;
        const uint32_t src = ring ? sb + SM_RING + slot * RSLOT : sb + SM_XQ + w * 8192;
        const uint32_t bytes = w == 2 ? 4096 : 8192;
        mbar_wait(sb + BAR_OSTAGE + w * 8, ph);
        bulk_store(dst + w * 8192, src, bytes);
        bulk_store(dst + XSLOT + w * 8192, src + (ring ? 8192 : XSLOT), bytes);
        asm volatile("cp.async.bulk.commit_group;" ::: "memory");
      }
      asm volatile("cp.async.bulk.wait_group.read 0;" ::: "memory");
      if (ring) {
#pragma unroll
        for (int w = 0; w < 3; ++w) {
          const uint32_t slot = (use - (w == 0 ? 2 : w == 1 ? 3 : 1)) % NRING;
          if ((w == 0) == (rank == 0))
            asm volatile("mbarrier.arrive.shared::cluster.b64 _, [%0], 3;" ::"r"(peer + BAR_PEMPTY + slot * 8) : "memory");
          asm volatile("mbarrier.arrive.shared::cta.b64 _, [%0], 3;" ::"r"(sb + BAR_EMPTY + slot * 8) : "memory");
        }
      } else {
        asm volatile("mbarrier.arrive.shared::cta.b64 _, [%0], 3;" ::"r"(sb + BAR_XEMPTY) : "memory");
        asm volatile("mbarrier.arrive.shared::cta.b64 _, [%0], 3;" ::"r"(sb + BAR_XEMPTY + 8) : "memory");
      }
    }
    if (item >= nitems - 2) {
      asm volatile("cp.async.bulk.wait_group 0;" ::: "memory");
      asm volatile("fence.proxy.async;" ::: "memory");
      asm volatile("red.release.gpu.global.add.u32 [%0], 3;" ::"l"(myflag + (item == nitems - 1)) : "memory");
    }
  }
}

struct Cursor {
  uint32_t slot, ph;
  __device__ __forceinline__ void adv() { if (++slot == NRING) { slot = 0; ph ^= 1; } }
  __device__ __forceinline__ void adv2() { slot += 2; if (slot >= NRING) { slot -= NRING; ph ^= 1; } }
};

__device__ __forceinline__ void release_ring(uint32_t sb, uint32_t slot, bool remote, uint32_t psb, bool elected) {
  mbar_arrive_remote_if(psb + BAR_PEMPTY + slot * 8, remote && elected);
  mbar_arrive_if(sb + BAR_EMPTY + slot * 8, elected);
}

template <int NG>
__device__ __forceinline__ void store_T(const float* a, uint32_t base_lane) {
#pragma unroll
  for (int g = 0; g < NG; g += 2)
    stsm_x4_t(base_lane + g * 1024, pack_bf16(a[4 * g], a[4 * g + 1]), pack_bf16(a[4 * g + 2], a[4 * g + 3]),
              pack_bf16(a[4 * g + 4], a[4 * g + 5]), pack_bf16(a[4 * g + 6], a[4 * g + 7]));
}

struct AttnCtx {
  uint32_t sb, peer, rank;
  int wg, warp, lane, bb;
  bool elected;
  __nv_bfloat16* oscr;
};

__device__ __forceinline__ bool mbar_try(uint32_t bar, uint32_t parity) {
  uint32_t ok;
  asm volatile("{\n.reg .pred p;\nmbarrier.try_wait.parity.shared::cta.b64 p, [%1], %2;\nselp.u32 %0, 1, 0, p;\n}"
               : "=r"(ok) : "r"(bar), "r"(parity) : "memory");
  return ok != 0;
}

template <bool HALF>
__device__ __forceinline__ void attention(const AttnCtx& A, Cursor& cur, int item, int h0, int nh) {
  const uint32_t sb = A.sb, peer = A.peer, rank = A.rank;
  const int wg = A.wg, lane = A.lane;
  const bool elected = A.elected;
  const int nblk = 8 * nh;
  const float CS = 0.08838834764831845f * 1.4426950408889634f;
  float o[64], s[32];
  uint32_t p[16], p2[16];
#pragma unroll
  for (int i = 0; i < 64; ++i) o[i] = 0.f;
#pragma unroll
  for (int i = 0; i < 32; ++i) s[i] = 0.f;
#pragma unroll
  for (int i = 0; i < 16; ++i) { p[i] = 0u; p2[i] = 0u; }
  float mc0 = 0.f, mc1 = 0.f, l0 = 0.f, l1 = 0.f;
  Cursor kc = cur, vc = cur; vc.adv();
  uint32_t stage0 = 0, stage1 = 0;
  const int qslot = nh == 2 ? 0 : 2;
  const uint64_t dq0 = make_desc(sb + SM_XQ + qslot * XSLOT + wg * 8192, 0, HALF ? 512 : 1024);
  const uint64_t dk0 = make_desc(sb + SM_RING, 0, 1024);
  const uint64_t dv0 = make_desc(sb + SM_RING, 8192, 1024);
  auto issue_qk = [&](int n) {
    const uint64_t dq = dq0 + (uint32_t)((n >> 3) * 2 * (XSLOT >> 4));
    const uint64_t dk = dk0 + kc.slot * (RSLOT >> 4);
    wg_fence();
#pragma unroll
    for (int kk = 0; kk < 8; ++kk)
      wgmma_ss_n64<0, 0>(s, dq + (kk >> 2) * (XSLOT >> 4) + (kk & 3) * 2, dk + (kk >> 2) * 512 + (kk & 3) * 2, kk != 0);
    wg_commit();
  };
  auto issue_pv = [&](int n, uint32_t (&pc)[16]) {
    const uint64_t dv = dv0 + vc.slot * (RSLOT >> 4);
    wg_fence();
#pragma unroll
    for (int kk = 0; kk < 4; ++kk)
      wgmma_rs_n128<1>(o, pc[4 * kk], pc[4 * kk + 1], pc[4 * kk + 2], pc[4 * kk + 3], dv + kk * 128, ((n & 7) | kk) != 0);
    wg_commit();
  };
  auto done_qk = [&](int n) {
    if (n == nblk - 1) {
      stage0 = kc.slot;
      mbar_arrive_if(sb + BAR_KVDONE, elected);
      mbar_arrive_if(sb + BAR_XEMPTY + 2 * 8, elected);
      mbar_arrive_if(sb + BAR_XEMPTY + 3 * 8, elected);
    } else {
      release_ring(sb, kc.slot, 2 * n + 9 >= 2 * nblk && rank == 0, peer, elected);
    }
    kc.adv2();
  };
  auto softmax = [&](bool first, uint32_t (&pn)[16], float& al0, float& al1) -> bool {
    bool upd = first;
    if (first) { l0 = 0.f; l1 = 0.f; }
    while (true) {
      if (upd) {
        float t0[8], t1[8];
#pragma unroll
        for (int g = 0; g < 8; ++g) { t0[g] = fmaxf(s[4 * g], s[4 * g + 1]); if (!HALF) t1[g] = fmaxf(s[4 * g + 2], s[4 * g + 3]); }
#pragma unroll
        for (int g = 0; g < 4; ++g) { t0[g] = fmaxf(t0[g], t0[g + 4]); if (!HALF) t1[g] = fmaxf(t1[g], t1[g + 4]); }
        float m0 = fmaxf(fmaxf(t0[0], t0[2]), fmaxf(t0[1], t0[3])), m1 = 0.f;
        if (!HALF) m1 = fmaxf(fmaxf(t1[0], t1[2]), fmaxf(t1[1], t1[3]));
        m0 = fmaxf(m0, __shfl_xor_sync(0xffffffffu, m0, 1));
        if (!HALF) m1 = fmaxf(m1, __shfl_xor_sync(0xffffffffu, m1, 1));
        m0 = fmaxf(m0, __shfl_xor_sync(0xffffffffu, m0, 2));
        if (!HALF) m1 = fmaxf(m1, __shfl_xor_sync(0xffffffffu, m1, 2));
        m0 *= CS; m1 *= CS;
        if (first) {
          mc0 = m0; mc1 = m1;
        } else {
          const float n0 = fmaxf(mc0, m0), n1 = fmaxf(mc1, m1);
          al0 = ex2(mc0 - n0);
          l0 *= al0; mc0 = n0;
          if (!HALF) { al1 = ex2(mc1 - n1); l1 *= al1; mc1 = n1; }
        }
      }
      float r0, r1 = 0.f;
      {
        float ra0 = 0.f, ra1 = 0.f, rb0 = 0.f, rb1 = 0.f;
#pragma unroll
        for (int g = 0; g < 8; ++g) {
          const float e0 = ex2(fmaf(s[4 * g], CS, -mc0)), e1 = ex2(fmaf(s[4 * g + 1], CS, -mc0));
          ra0 += e0; rb0 += e1;
          pn[2 * g] = pack_bf16(e0, e1);
          if (!HALF) {
            const float e2 = ex2(fmaf(s[4 * g + 2], CS, -mc1)), e3 = ex2(fmaf(s[4 * g + 3], CS, -mc1));
            ra1 += e2; rb1 += e3;
            pn[2 * g + 1] = pack_bf16(e2, e3);
          }
        }
        r0 = ra0 + rb0;
        if (!HALF) r1 = ra1 + rb1;
      }
      if (!upd && __any_sync(0xffffffffu, !(r0 <= 256.f) || !(r1 <= 256.f))) { upd = true; continue; }
      l0 += r0; l1 += r1;
      break;
    }
    return upd && !first;
  };
  auto epilogue = [&](bool ring, uint32_t tile, float lf0, float lf1) {
    lf0 += __shfl_xor_sync(0xffffffffu, lf0, 1);
    if (!HALF) lf1 += __shfl_xor_sync(0xffffffffu, lf1, 1);
    lf0 += __shfl_xor_sync(0xffffffffu, lf0, 2);
    if (!HALF) lf1 += __shfl_xor_sync(0xffffffffu, lf1, 2);
    const float i0 = rcp_fast(lf0), i1 = HALF ? 0.f : rcp_fast(lf1);
    const uint32_t cstride = ring ? 8192 : XSLOT;
    const int mi = lane >> 3, i8 = lane & 7;
    if (!HALF) {
      const uint32_t rowa = tile + (A.warp * 16 + 8 * (mi & 1) + i8) * 128;
#pragma unroll
      for (int g = 0; g < 16; g += 2)
        stsm_x4(rowa + (g >> 3) * cstride + ((((g & 7) + (mi >> 1)) ^ i8) << 4),
                pack_bf16(o[4 * g] * i0, o[4 * g + 1] * i0), pack_bf16(o[4 * g + 2] * i1, o[4 * g + 3] * i1),
                pack_bf16(o[4 * g + 4] * i0, o[4 * g + 5] * i0), pack_bf16(o[4 * g + 6] * i1, o[4 * g + 7] * i1));
    } else {
      const uint32_t rowa = tile + (A.warp * 8 + i8) * 128;
#pragma unroll
      for (int g = 0; g < 16; g += 4)
        stsm_x4(rowa + (g >> 3) * cstride + ((((g & 7) + mi) ^ i8) << 4),
                pack_bf16(o[4 * g] * i0, o[4 * g + 1] * i0), pack_bf16(o[4 * g + 4] * i0, o[4 * g + 5] * i0),
                pack_bf16(o[4 * g + 8] * i0, o[4 * g + 9] * i0), pack_bf16(o[4 * g + 12] * i0, o[4 * g + 13] * i0));
    }
    asm volatile("fence.proxy.async.shared::cta;" ::: "memory");
    __syncwarp();
    mbar_arrive_if(sb + BAR_OSTAGE + wg * 8, lane == 0);
  };

  const int pp_next = wg == 2 ? 0 : wg + 1;
  const bool pp_last = wg == 2;
  float al0 = 1.f, al1 = 1.f;
  mbar_wait(sb + BAR_FULL + kc.slot * 8, kc.ph);
  if (wg != 0) bar_sync(8 + wg, 256);
  issue_qk(0);
  asm volatile("bar.arrive %0, %1;" ::"r"(8 + pp_next), "r"(256) : "memory");
  wg_wait<0>();
  fence_regs(s);
  done_qk(0);
  softmax(true, p, al0, al1);
  mbar_wait(sb + BAR_FULL + kc.slot * 8, kc.ph);
  mbar_wait(sb + BAR_FULL + vc.slot * 8, vc.ph);
  auto step = [&](int n, uint32_t (&pc)[16], uint32_t (&pn)[16], bool last) {
    bar_sync(8 + wg, 256);
    issue_qk(n + 1);
    issue_pv(n, pc);
    if (!(last && pp_last)) asm volatile("bar.arrive %0, %1;" ::"r"(8 + pp_next), "r"(256) : "memory");
    wg_wait<1>();
    fence_regs(s);
    done_qk(n + 1);
    Cursor vn = vc; vn.adv2();
    const bool kok = last || mbar_try(sb + BAR_FULL + kc.slot * 8, kc.ph);
    const bool vok = mbar_try(sb + BAR_FULL + vn.slot * 8, vn.ph);
    const bool head_end = (n & 7) == 7;
    const float lf0 = l0, lf1 = l1;
    const bool resc = softmax(head_end, pn, al0, al1);
    fence_regs(pn);
    wg_wait<0>();
    fence_regs(o);
    fence_regs(pc);
    if (last) { stage1 = vc.slot; mbar_arrive_if(sb + BAR_KVDONE + 8, elected); }
    else release_ring(sb, vc.slot, 2 * n + 10 >= 2 * nblk && rank == 1, peer, elected);
    vc = vn;
    if (head_end) {
      epilogue(false, sb + SM_XQ + wg * 8192, lf0, lf1);
    } else if (resc) {
#pragma unroll
      for (int g = 0; g < 16; ++g) {
        o[4 * g] *= al0; o[4 * g + 1] *= al0;
        if (!HALF) { o[4 * g + 2] *= al1; o[4 * g + 3] *= al1; }
      }
    }
    if (!kok) mbar_wait(sb + BAR_FULL + kc.slot * 8, kc.ph);
    if (!vok) mbar_wait(sb + BAR_FULL + vc.slot * 8, vc.ph);
  };
  for (int n = 0; n < nblk - 2; n += 2) {
    step(n, p, p2, false);
    step(n + 1, p2, p, false);
  }
  step(nblk - 2, p, p2, true);
  issue_pv(nblk - 1, p2);
  wg_wait<0>();
  fence_regs(o);
  mbar_arrive_if(sb + BAR_KVDONE + 16, elected);
  mbar_wait(sb + BAR_KVDONE + wg * 8, item & 1);
  epilogue(true, sb + SM_RING + (wg == 0 ? stage0 : wg == 1 ? stage1 : vc.slot) * RSLOT, l0, l1);
  cur = kc;
}

__device__ __forceinline__ void consumer(const KParams& P, uint32_t sb, int wg, int blk, int b, int j, uint32_t rank,
                                         __nv_bfloat16* __restrict__ oscr, unsigned int* flags) {
  const int tid = threadIdx.x & 127;
  const int warp = tid >> 5, lane = tid & 31;
  const bool elected = tid == 0;
  const uint32_t peer = __shfl_sync(0xffffffffu, mapa(sb, rank ^ 1), 0);
  Cursor cur{0, 0};
  uint32_t xg = 0;

  const bool stag = (j & 1) != 0;
  const int nitems = stag ? 5 : 4;
  const AttnCtx A{sb, peer, rank, wg, warp, lane, blk * NBATCH + b, elected, oscr};

  for (int item = 0; item <= nitems; ++item) {
    const bool ph2 = item == nitems;
    const int nk = ph2 ? 64 : 16;
    const int nh = ph2 ? 2 : item_heads(stag, item);
    {
      float a0[80], a1[40];
#pragma unroll
      for (int i = 0; i < 80; ++i) a0[i] = 0.f;
#pragma unroll
      for (int i = 0; i < 40; ++i) a1[i] = 0.f;
      const int rem_lim = 2 * nk - 9;
      uint32_t pslotA = 0, pslotB = 0, pxs = 0;
      auto rel_prev = [&](int ks) {
        const int off = 2 * (ks - 1);
        release_ring(sb, pslotA, off < rem_lim && rank == 0, peer, elected);
        release_ring(sb, pslotB, off + 1 < rem_lim && rank == 1, peer, elected);
        mbar_arrive_if(sb + BAR_XEMPTY + pxs * 8, ks - 1 < nk - 4 && elected);
      };
      if (nh == 2 && wg < 2) {
        for (int ks = 0; ks < nk; ++ks) {
          const uint32_t sA = cur.slot, phA = cur.ph; cur.adv();
          const uint32_t sB = cur.slot, phB = cur.ph; cur.adv();
          const uint32_t xs = xg & 3;
          mbar_wait(sb + BAR_FULL + sA * 8, phA);
          mbar_wait(sb + BAR_FULL + sB * 8, phB);
          mbar_wait(sb + BAR_XFULL + xs * 8, (xg >> 2) & 1);
          const uint32_t xb = sb + SM_XQ + xs * XSLOT;
          const uint64_t dA = make_desc(sb + SM_RING + sA * RSLOT + wg * 8192, 0, 1024);
          const uint64_t dA3 = make_desc(sb + SM_RING + sB * RSLOT + 8192, 0, 1024);
          const uint64_t dB = make_desc(xb, 0, 1024), dB3 = make_desc(xb + wg * 10240, 0, 1024);
          wg_fence();
#pragma unroll
          for (int kk = 0; kk < 4; ++kk) {
            const int sd = (ks | kk) != 0;
            wgmma_ss_n160<1, 0>(a0, dA + kk * 128, dB + kk * 2, sd);
            wgmma_ss_n80<1, 0>(a1, dA3 + kk * 128, dB3 + kk * 2, sd);
          }
          wg_commit();
          if (ks > 0) { wg_wait<1>(); rel_prev(ks); }
          pslotA = sA; pslotB = sB; pxs = xs;
          ++xg;
        }
        wg_wait<0>();
        fence_regs(a0); fence_regs(a1);
      } else if (nh == 2 || wg < 2) {
        for (int ks = 0; ks < nk; ++ks) {
          const uint32_t sA = cur.slot, phA = cur.ph; cur.adv();
          const uint32_t sB = cur.slot, phB = cur.ph; cur.adv();
          const uint32_t xs = xg & 3;
          mbar_wait(sb + BAR_FULL + sA * 8, phA);
          mbar_wait(sb + BAR_FULL + sB * 8, phB);
          mbar_wait(sb + BAR_XFULL + xs * 8, (xg >> 2) & 1);
          const uint64_t dA = make_desc(sb + SM_RING + (wg == 0 ? sA : sB) * RSLOT, 0, 1024);
          const uint64_t dB = make_desc(sb + SM_XQ + xs * XSLOT, 0, 1024);
          wg_fence();
#pragma unroll
          for (int kk = 0; kk < 4; ++kk) wgmma_ss_n160<1, 0>(a0, dA + kk * 128, dB + kk * 2, (ks | kk) != 0);
          wg_commit();
          if (ks > 0) { wg_wait<1>(); rel_prev(ks); }
          pslotA = sA; pslotB = sB; pxs = xs;
          ++xg;
        }
        wg_wait<0>();
        fence_regs(a0);
      } else {
        for (int ks = 0; ks < nk; ++ks) {
          const uint32_t sA = cur.slot, phA = cur.ph; cur.adv();
          const uint32_t sB = cur.slot, phB = cur.ph; cur.adv();
          const uint32_t xs = xg & 3;
          if (ks > 0) rel_prev(ks);
          mbar_wait(sb + BAR_FULL + sA * 8, phA);
          mbar_wait(sb + BAR_FULL + sB * 8, phB);
          mbar_wait(sb + BAR_XFULL + xs * 8, (xg >> 2) & 1);
          pslotA = sA; pslotB = sB; pxs = xs;
          ++xg;
        }
      }
      release_ring(sb, pslotA, false, peer, elected);
      release_ring(sb, pslotB, false, peer, elected);
      bar_sync(1, 384);
      const int mi = lane >> 3, i8 = lane & 7;
      const uint32_t lane_off = (8 * (mi >> 1) + i8) * 128 + (((2 * warp + (mi & 1)) ^ i8) << 4);
      if (nh == 2 || wg < 2) store_T<20>(a0, sb + SM_XQ + (nh == 2 ? wg : wg + 2) * XSLOT + lane_off);
      if (nh == 2) {
        if (wg < 2) store_T<10>(a1, sb + SM_XQ + 3 * XSLOT + wg * 10240 + lane_off);
      } else {
        mbar_arrive_if(sb + BAR_XEMPTY + 0 * 8, elected);
        mbar_arrive_if(sb + BAR_XEMPTY + 1 * 8, elected);
      }
      asm volatile("fence.proxy.async.shared::cta;" ::: "memory");
      if (ph2) {
        bar_sync(2 + wg, 128);
        if (elected) {
          tma_store_2d(&P.out, sb + SM_XQ + wg * XSLOT, blk * 1024 + 256 * j + 64 * wg, SQ * b);
          asm volatile("cp.async.bulk.commit_group;" ::: "memory");
        }
        if (wg < 2) {
          bar_sync(5, 256);
          if (wg == 0 && elected) {
            tma_store_2d(&P.out, sb + SM_XQ + 3 * XSLOT, blk * 1024 + 256 * j + 192, SQ * b);
            asm volatile("cp.async.bulk.commit_group;" ::: "memory");
          }
        }
        if (elected) asm volatile("cp.async.bulk.wait_group.read 0;" ::: "memory");
      } else {
        bar_sync(1, 384);
      }
    }
    if (ph2) break;
    const int h0 = 8 * j + item_head0(stag, item);
    if (wg == 2) attention<true>(A, cur, item, h0, nh);
    else attention<false>(A, cur, item, h0, nh);
  }
}

__global__ void __cluster_dims__(2, 1, 1) __launch_bounds__(NTHREADS, 1)
fused_mha_kernel(const __grid_constant__ KParams P, __nv_bfloat16* __restrict__ oscr, unsigned int* flags) {
  extern __shared__ uint8_t smem_raw[];
  const uint32_t sb = __shfl_sync(0xffffffffu, (smem_u32(smem_raw) + 1023) & ~1023u, 0);
  const int wg = __shfl_sync(0xffffffffu, threadIdx.x >> 7, 0);
  uint32_t rank;
  asm("mov.u32 %0, %%cluster_ctarank;" : "=r"(rank));
  const int c = blockIdx.x >> 1;
  const int blk = c >> 5, pr = (c & 31) >> 2, j = c & 3;
  const int b = 2 * pr + (int)rank;
  if (threadIdx.x == 32) {
    asm volatile("prefetch.tensormap [%0];" ::"l"(&P.x[blk]) : "memory");
    asm volatile("prefetch.tensormap [%0];" ::"l"(&P.wq[blk]) : "memory");
    asm volatile("prefetch.tensormap [%0];" ::"l"(&P.k[blk]) : "memory");
    asm volatile("prefetch.tensormap [%0];" ::"l"(&P.v[blk]) : "memory");
  }
  if (threadIdx.x == 0) {
    for (int i = 0; i < NRING; ++i) { mbar_init(sb + BAR_FULL + i * 8, 1); mbar_init(sb + BAR_EMPTY + i * 8, 3); mbar_init(sb + BAR_PEMPTY + i * 8, 3); }
    for (int i = 0; i < 4; ++i) { mbar_init(sb + BAR_XFULL + i * 8, 1); mbar_init(sb + BAR_XEMPTY + i * 8, 3); }
    for (int i = 0; i < 3; ++i) { mbar_init(sb + BAR_OSTAGE + i * 8, 4); mbar_init(sb + BAR_KVDONE + i * 8, 3); }
    asm volatile("st.volatile.shared.u32 [%0], %1;" ::"r"(sb + SM_ABORT), "r"(0u) : "memory");
    asm volatile("fence.mbarrier_init.release.cluster;" ::: "memory");
  }
  __syncthreads();
  asm volatile("barrier.cluster.arrive.release;" ::: "memory");
  if (wg == 3) {
    asm volatile("setmaxnreg.dec.sync.aligned.u32 32;");
    const int warp = __shfl_sync(0xffffffffu, threadIdx.x >> 5, 0);
    if (warp == 13) {
      producer_x(P, sb, blk, b, j, flags, oscr);
      asm volatile("barrier.cluster.wait.acquire;" ::: "memory");
    } else {
      asm volatile("barrier.cluster.wait.acquire;" ::: "memory");
      if (warp == 12) producer_ring(P, sb, blk, b, j, rank);
      else if (warp == 14) store_warp(sb, mapa(sb, rank ^ 1), rank, blk, b, j, flags, oscr);
    }
  } else {
    asm volatile("setmaxnreg.inc.sync.aligned.u32 160;");
    asm volatile("barrier.cluster.wait.acquire;" ::: "memory");
    consumer(P, sb, wg, blk, b, j, rank, oscr, flags);
  }
}

typedef CUresult (*EncodeFn)(CUtensorMap*, CUtensorMapDataType, cuuint32_t, void*, const cuuint64_t*, const cuuint64_t*,
                             const cuuint32_t*, const cuuint32_t*, CUtensorMapInterleave, CUtensorMapSwizzle,
                             CUtensorMapL2promotion, CUtensorMapFloatOOBfill);

bool encode(EncodeFn fn, CUtensorMap* tm, const void* base, int rank, const cuuint64_t* dims, const cuuint64_t* strides,
            const cuuint32_t* box, CUtensorMapL2promotion promo = CU_TENSOR_MAP_L2_PROMOTION_L2_256B) {
  cuuint32_t es[5] = {1, 1, 1, 1, 1};
  CUresult r = fn(tm, CU_TENSOR_MAP_DATA_TYPE_BFLOAT16, rank, const_cast<void*>(base), dims, strides, box, es,
                  CU_TENSOR_MAP_INTERLEAVE_NONE, CU_TENSOR_MAP_SWIZZLE_128B, promo,
                  CU_TENSOR_MAP_FLOAT_OOB_FILL_NONE);
  return r == CUDA_SUCCESS;
}

}

extern "C" void kernel_launch(void* const* d_in, const int* in_sizes, int n_in, void* d_out, int out_size) {
  (void)in_sizes; (void)n_in; (void)out_size;
  static KParams P;
  static bool ready = false;
  static __nv_bfloat16* oscr = nullptr;
  static unsigned int* flags = nullptr;
  static const void* last_ptrs[11] = {};
  bool same = ready;
  for (int i = 0; i < 10; ++i) same = same && last_ptrs[i] == d_in[i];
  same = same && last_ptrs[10] == d_out;
  if (!same) {
    void* fnp = nullptr;
    cudaDriverEntryPointQueryResult qr;
    cudaGetDriverEntryPoint("cuTensorMapEncodeTiled", &fnp, cudaEnableDefault, &qr);
    EncodeFn fn = (EncodeFn)fnp;
    cudaGetSymbolAddress((void**)&oscr, g_o);
    cudaGetSymbolAddress((void**)&flags, g_flags);
    bool ok = fn != nullptr;
    for (int blk = 0; blk < 2 && ok; ++blk) {
      const void* x = d_in[5 * blk + 0]; const void* k = d_in[5 * blk + 1]; const void* v = d_in[5 * blk + 2];
      const void* wq = d_in[5 * blk + 3]; const void* wo = d_in[5 * blk + 4];
      { cuuint64_t d[2] = {1024, 2560}, s[1] = {2048}; cuuint32_t bx[2] = {64, 160}; ok = ok && encode(fn, &P.x[blk], x, 2, d, s, bx, CU_TENSOR_MAP_L2_PROMOTION_L2_256B); }
      { cuuint64_t d[2] = {4096, 1024}, s[1] = {8192}; cuuint32_t bx[2] = {64, 64}; ok = ok && encode(fn, &P.wq[blk], wq, 2, d, s, bx, CU_TENSOR_MAP_L2_PROMOTION_L2_128B); }
      { cuuint64_t d[2] = {128, 262144}, s[1] = {256}; cuuint32_t bx[2] = {64, 64};
        ok = ok && encode(fn, &P.k[blk], k, 2, d, s, bx, CU_TENSOR_MAP_L2_PROMOTION_L2_128B); ok = ok && encode(fn, &P.v[blk], v, 2, d, s, bx, CU_TENSOR_MAP_L2_PROMOTION_L2_128B); }
      { cuuint64_t d[2] = {1024, 4096}, s[1] = {2048}; cuuint32_t bx[2] = {64, 64}; ok = ok && encode(fn, &P.wo[blk], wo, 2, d, s, bx, CU_TENSOR_MAP_L2_PROMOTION_L2_128B); }
    }
    { cuuint64_t d[2] = {2048, 2560}, s[1] = {4096}; cuuint32_t bx[2] = {64, 160}; ok = ok && encode(fn, &P.out, d_out, 2, d, s, bx); }
    if (!ok) { ready = false; return; }
    cudaFuncSetAttribute(fused_mha_kernel, cudaFuncAttributeMaxDynamicSharedMemorySize, SMEM_BYTES);
    for (int i = 0; i < 10; ++i) last_ptrs[i] = d_in[i];
    last_ptrs[10] = d_out;
    ready = true;
  }
  fused_mha_kernel<<<NCTA, NTHREADS, SMEM_BYTES, cudaStreamPerThread>>>(P, oscr, flags);
}
```
